```python
import torch

def _softmax(x, axis=-1):
    return torch.softmax(x, dim=axis)
def _gelu(x):
    return torch.nn.functional.gelu(x, approximate="tanh")
def _silu(x):
    return torch.nn.functional.silu(x)
def _sigmoid(x):
    return torch.sigmoid(x)
def _layernorm(x, axis=-1, eps=1e-5):
    m = x.mean(dim=axis, keepdim=True)
    v = x.var(dim=axis, keepdim=True, unbiased=False)
    return (x - m) / torch.sqrt(v + eps)
def _scatter_add(tgt, idx, src, axis=0):
    return tgt.clone().index_add_(axis, idx, src)
def _segment_sum(src, seg, n):
    out = torch.zeros((n,) + src.shape[1:], dtype=src.dtype)
    return out.index_add_(0, seg, src)
def _pad(x, pw):
    flat = tuple(v for pair in reversed(pw) for v in pair)
    return torch.nn.functional.pad(x, flat)

kernel_name = 'standalone__standard_2d_1d_3d_conv__vision'

def setup_inputs():

    _w = (lambda a: (lambda t: t.to(torch.bfloat16) if t.is_floating_point() else t)(torch.as_tensor(a)))
    H = W = 512
    C = 96
    K = 3
    return {
        "x": _w((lambda *s: torch.randn(*s, dtype=torch.bfloat16) * 0.05)(1, H, W, C)),
        "w": _w((lambda *s: torch.randn(*s, dtype=torch.bfloat16) * 0.05)(K, K, C, C)),
        "b": _w((lambda *s: torch.randn(*s, dtype=torch.bfloat16) * 0.05)(C)),
    }

def reference(x, w, b):
    B, H, W, Cin = x.shape
    K = w.shape[0]
    pl = (K - 1) // 2
    pr = K // 2
    xp = _pad(x, ((0, 0), (pl, pr), (pl, pr), (0, 0)))
    out = sum(
        torch.einsum('bhwc,cd->bhwd', xp[:, i:i+H, j:j+W, :], w[i, j])
        for i in range(K) for j in range(K)
    )
    return out + b[None, None, None, :]
```

```cpp
#include <cuda_runtime.h>
#include <cuda_bf16.h>
#include <cuda.h>
#include <stdint.h>
#include <type_traits>

#define DEVI __device__ __forceinline__

namespace {

constexpr int IMG_H = 512, IMG_W = 512, CH = 96;
constexpr int ROW_LINES = 100;
constexpr int ROW_TX = ROW_LINES * 128;
constexpr int ROW_PITCH = 13312;
constexpr int STAGE_BYTES = 2 * ROW_PITCH;
constexpr int RING_BYTES = 2 * STAGE_BYTES;
constexpr int W_OFF = 2 * RING_BYTES;
constexpr int WBLK = 1536;
constexpr int W_BYTES = 72 * WBLK;
constexpr int BAR_OFF = W_OFF + W_BYTES;
constexpr int SMEM_BYTES = BAR_OFF + 128;
constexpr uint32_t SMEM_BASE = 1024;
constexpr int NUM_THREADS = 384;

DEVI uint32_t smem_u32(const void* p) { return (uint32_t)__cvta_generic_to_shared(p); }
DEVI void wg_fence() { asm volatile("wgmma.fence.sync.aligned;" ::: "memory"); }
DEVI void wg_commit() { asm volatile("wgmma.commit_group.sync.aligned;" ::: "memory"); }
template <int N> DEVI void wg_wait() { asm volatile("wgmma.wait_group.sync.aligned %0;" ::"n"(N) : "memory"); }

DEVI void ldsm4(uint32_t (&r)[4], uint32_t addr) {
  asm volatile("ldmatrix.sync.aligned.m8n8.x4.shared.b16 {%0,%1,%2,%3}, [%4];"
               : "=r"(r[0]), "=r"(r[1]), "=r"(r[2]), "=r"(r[3]) : "r"(addr) : "memory");
}
DEVI void stsm4(uint32_t addr, uint32_t r0, uint32_t r1, uint32_t r2, uint32_t r3) {
  asm volatile("stmatrix.sync.aligned.m8n8.x4.shared.b16 [%0], {%1,%2,%3,%4};"
               ::"r"(addr), "r"(r0), "r"(r1), "r"(r2), "r"(r3) : "memory");
}
DEVI uint32_t hadd2(uint32_t a, uint32_t b) { uint32_t r; asm volatile("add.rn.bf16x2 %0, %1, %2;" : "=r"(r) : "r"(a), "r"(b)); return r; }
DEVI uint32_t hsub2(uint32_t a, uint32_t b) { uint32_t r; asm volatile("sub.rn.bf16x2 %0, %1, %2;" : "=r"(r) : "r"(a), "r"(b)); return r; }
DEVI uint32_t mov32(uint32_t a) { uint32_t r; asm volatile("mov.b32 %0, %1;" : "=r"(r) : "r"(a)); return r; }
DEVI uint32_t pack_bf16(float lo, float hi) { uint32_t r; asm("cvt.rn.bf16x2.f32 %0, %1, %2;" : "=r"(r) : "f"(hi), "f"(lo)); return r; }
DEVI float bf_lo(uint32_t v) { return __uint_as_float(v << 16); }
DEVI float bf_hi(uint32_t v) { return __uint_as_float(v & 0xffff0000u); }

DEVI void mbar_init(uint32_t bar, uint32_t cnt) { asm volatile("mbarrier.init.shared::cta.b64 [%0], %1;" ::"r"(bar), "r"(cnt) : "memory"); }
DEVI void mbar_arrive(uint32_t bar) { asm volatile("mbarrier.arrive.shared::cta.b64 _, [%0];" ::"r"(bar) : "memory"); }
DEVI void mbar_expect_tx(uint32_t bar, uint32_t tx) { asm volatile("mbarrier.arrive.expect_tx.shared::cta.b64 _, [%0], %1;" ::"r"(bar), "r"(tx) : "memory"); }
DEVI bool mbar_try(uint32_t bar, uint32_t parity) {
  uint32_t ok;
  asm volatile("{\n.reg .pred p;\nmbarrier.try_wait.parity.shared::cta.b64 p, [%1], %2;\nselp.b32 %0, 1, 0, p;\n}\n"
               : "=r"(ok) : "r"(bar), "r"(parity) : "memory");
  return ok != 0;
}
DEVI void mbar_wait(uint32_t bar, uint32_t parity) {
  if (mbar_try(bar, parity)) return;
  for (uint32_t it = 0; !mbar_try(bar, parity); ++it)
    if (it > (1u << 22)) __trap();
}
DEVI void tma_row(uint32_t dst, const CUtensorMap* map, int line, int y, uint32_t bar) {
  asm volatile("cp.async.bulk.tensor.3d.shared::cluster.global.mbarrier::complete_tx::bytes [%0], [%1, {%3, %4, %5}], [%2];"
               ::"r"(dst), "l"(map), "r"(bar), "r"(0), "r"(line), "r"(y) : "memory");
}

template <int ACC>
DEVI void mma48(float (&d)[24], const uint32_t (&a)[4], int blk) {
  const uint64_t desc = (uint64_t)((SMEM_BASE + W_OFF + blk * WBLK) >> 4) | ((uint64_t)(768 >> 4) << 16) | ((uint64_t)(128 >> 4) << 32);
  asm volatile(
      "wgmma.mma_async.sync.aligned.m64n48k16.f32.bf16.bf16 "
      "{%0,%1,%2,%3,%4,%5,%6,%7,%8,%9,%10,%11,%12,%13,%14,%15,%16,%17,%18,%19,%20,%21,%22,%23}, "
      "{%24,%25,%26,%27}, %28, %29, 1, 1, 1;\n"
      : "+f"(d[0]), "+f"(d[1]), "+f"(d[2]), "+f"(d[3]), "+f"(d[4]), "+f"(d[5]), "+f"(d[6]), "+f"(d[7]),
        "+f"(d[8]), "+f"(d[9]), "+f"(d[10]), "+f"(d[11]), "+f"(d[12]), "+f"(d[13]), "+f"(d[14]), "+f"(d[15]),
        "+f"(d[16]), "+f"(d[17]), "+f"(d[18]), "+f"(d[19]), "+f"(d[20]), "+f"(d[21]), "+f"(d[22]), "+f"(d[23])
      : "r"(a[0]), "r"(a[1]), "r"(a[2]), "r"(a[3]), "l"(desc), "n"(ACC));
}

DEVI void st128(void* p, uint32_t a, uint32_t b, uint32_t c, uint32_t d) {
  asm volatile("st.global.v4.b32 [%0], {%1,%2,%3,%4};" ::"l"(p), "r"(a), "r"(b), "r"(c), "r"(d) : "memory");
}
DEVI void st64(void* p, uint32_t a, uint32_t b) {
  asm volatile("st.global.v2.b32 [%0], {%1,%2};" ::"l"(p), "r"(a), "r"(b) : "memory");
}

__global__ void __launch_bounds__(NUM_THREADS, 1)
conv3x3_kernel(const __grid_constant__ CUtensorMap xmap, const __nv_bfloat16* __restrict__ wgt,
               const __nv_bfloat16* __restrict__ bias, __nv_bfloat16* __restrict__ out) {
  extern __shared__ __align__(1024) uint8_t smem_raw[];
  const uint32_t sbase = smem_u32(smem_raw);
  if ((sbase & 0xFFFFFFu) != SMEM_BASE) __trap();
  const uint32_t bars = sbase + BAR_OFF;
  const int tid = threadIdx.x, warp = __shfl_sync(0xffffffffu, tid >> 5, 0), lane = tid & 31;
  const int half = blockIdx.x & 1, pair = blockIdx.x >> 1;
  constexpr int NB = 16;

  if (tid == 256) {
    for (int i = 0; i < 4; ++i) { mbar_init(bars + 8 * i, 1); mbar_init(bars + 32 + 8 * i, 4); }
    asm volatile("fence.mbarrier_init.release.cluster;" ::: "memory");
    asm volatile("fence.proxy.async.shared::cta;" ::: "memory");
    for (int wg = 0; wg < 2; ++wg) {
      const int run = pair * 2 + wg;
      const int line0 = (run & 7) * 96 - 2, r0 = (run >> 3) * (2 * NB);
      const uint32_t ring = sbase + wg * RING_BYTES, fb = bars + wg * 16;
      mbar_expect_tx(fb, ROW_TX);
      tma_row(ring + ROW_PITCH, &xmap, line0, r0 - 1, fb);
      mbar_expect_tx(fb + 8, 2 * ROW_TX);
      tma_row(ring + STAGE_BYTES, &xmap, line0, r0, fb + 8);
      tma_row(ring + STAGE_BYTES + ROW_PITCH, &xmap, line0, r0 + 1, fb + 8);
    }
  }

  {
    const int g = lane >> 2, t4 = lane & 3, cg = warp;
    uint32_t raw[3][3][6];
#pragma unroll
    for (int kw = 0; kw < 3; ++kw)
#pragma unroll
      for (int kh = 0; kh < 3; ++kh) {
        const __nv_bfloat16* p = wgt + (size_t)((kh * 3 + kw) * CH + cg * 8 + g) * CH + half * 48;
        const uint4 v = __ldg(reinterpret_cast<const uint4*>(p + 8 * t4));
        const uint2 u = __ldg(reinterpret_cast<const uint2*>(p + 32 + 4 * t4));
        raw[kw][kh][0] = v.x; raw[kw][kh][1] = v.y; raw[kw][kh][2] = v.z; raw[kw][kh][3] = v.w;
        raw[kw][kh][4] = u.x; raw[kw][kh][5] = u.y;
      }
#pragma unroll
    for (int kw = 0; kw < 3; ++kw) {
      uint32_t u1[6], u2[6];
#pragma unroll
      for (int j = 0; j < 6; ++j) {
        const float tl = bf_lo(raw[kw][0][j]) + bf_lo(raw[kw][2][j]), th = bf_hi(raw[kw][0][j]) + bf_hi(raw[kw][2][j]);
        const float ml = bf_lo(raw[kw][1][j]), mh = bf_hi(raw[kw][1][j]);
        u1[j] = pack_bf16(tl + ml, th + mh);
        u2[j] = pack_bf16(tl - ml, th - mh);
      }
      const int step = (kw == 1) ? 2 : (cg & 1), khalf = (kw == 1) ? (cg & 1) : (kw >> 1);
      const uint32_t dst = sbase + W_OFF + (((cg >> 1) * 3 + step) * 4) * WBLK + khalf * 768;
      const uint32_t d4 = dst + lane * 16;
      const uint32_t d2 = dst + 512 + (lane & 15) * 16 + (lane >> 4) * WBLK;
      stsm4(d4, raw[kw][2][0], raw[kw][2][1], raw[kw][2][2], raw[kw][2][3]);
      stsm4(d4 + WBLK, u1[0], u1[1], u1[2], u1[3]);
      stsm4(d4 + 2 * WBLK, u2[0], u2[1], u2[2], u2[3]);
      stsm4(d4 + 3 * WBLK, raw[kw][0][0], raw[kw][0][1], raw[kw][0][2], raw[kw][0][3]);
      stsm4(d2, raw[kw][2][4], raw[kw][2][5], u1[4], u1[5]);
      stsm4(d2 + 2 * WBLK, u2[4], u2[5], raw[kw][0][4], raw[kw][0][5]);
    }
    asm volatile("fence.proxy.async.shared::cta;" ::: "memory");
  }
  __syncthreads();

  if (warp >= 8) {
    asm volatile("setmaxnreg.dec.sync.aligned.u32 24;");
    if (warp < 10 && lane == 0) {
      const int wg = warp - 8;
      const int run = pair * 2 + wg;
      const int line0 = (run & 7) * 96 - 2, r0 = (run >> 3) * (2 * NB);
      const uint32_t ring = sbase + wg * RING_BYTES, fb = bars + wg * 16, eb = fb + 32;
      for (int i = 2; i <= NB + 1; ++i) {
        const int s = i & 1;
        mbar_wait(eb + 8 * s, ((i >> 1) - 1) & 1);
        const int y = r0 + 2 * (i - 1);
        const uint32_t dst = ring + s * STAGE_BYTES;
        if (i <= NB) {
          mbar_expect_tx(fb + 8 * s, 2 * ROW_TX);
          tma_row(dst, &xmap, line0, y, fb + 8 * s);
          tma_row(dst + ROW_PITCH, &xmap, line0, y + 1, fb + 8 * s);
        } else {
          mbar_expect_tx(fb + 8 * s, ROW_TX);
          tma_row(dst, &xmap, line0, y, fb + 8 * s);
        }
      }
    }
  } else {
    asm volatile("setmaxnreg.inc.sync.aligned.u32 240;");
    const int wg = warp >> 2, w = warp & 3;
    const int run = pair * 2 + wg;
    const int x0 = (run & 7) * 64, r0 = (run >> 3) * (2 * NB);
    const uint32_t fb = bars + wg * 16, eb = fb + 32;
    const int g = lane >> 2, t4 = lane & 3;

    uint32_t aq[3];
    {
      const int p = 16 * w + 2 * (lane & 7) - 1 + (lane >> 3);
#pragma unroll
      for (int q = 0; q < 3; ++q) {
        const uint32_t off = 192 * p + 256 + 64 * q;
        aq[q] = sbase + wg * RING_BYTES + (off ^ (((off >> 7) & 7) << 4));
      }
    }
    float b2[12];
    {
      const uint4 v = __ldg(reinterpret_cast<const uint4*>(bias + half * 48 + 8 * t4));
      const uint2 u = __ldg(reinterpret_cast<const uint2*>(bias + half * 48 + 32 + 4 * t4));
      const uint32_t r[6] = {v.x, v.y, v.z, v.w, u.x, u.y};
#pragma unroll
      for (int j = 0; j < 6; ++j) { b2[2 * j] = 2.f * bf_lo(r[j]); b2[2 * j + 1] = 2.f * bf_hi(r[j]); }
    }
    uint8_t* optr = reinterpret_cast<uint8_t*>(out) + ((size_t)(r0 - 1) * IMG_W + x0 + 16 * w + 2 * g) * (CH * 2) + half * 96;
    constexpr int OROW = IMG_W * CH * 2;

    float Z0[24], Z1[24], Z2[24], Z3[24];
    uint32_t A[14][4], B[14][4], S[13][4], D[13][4], MA[7][4], MB[7][4], MS[7][4], MD[7][4];
    uint32_t yo[12], ye[12];

    auto ld_addr = [&](int cg) { return aq[cg >> 2] ^ (uint32_t)((cg & 3) << 4); };

    auto quarter = [&](float (&Z)[24], auto pos_c, auto acc_c, uint32_t rowoff) {
      constexpr int POS = decltype(pos_c)::value;
      constexpr int ACC = decltype(acc_c)::value;
      uint32_t F[12][4], M[6][4];
#pragma unroll
      for (int cg = 0; cg < 12; ++cg) ldsm4(F[cg], ld_addr(cg) + rowoff);
#pragma unroll
      for (int c = 0; c < 6; ++c) {
        M[c][0] = F[2 * c][1]; M[c][1] = F[2 * c][2]; M[c][2] = F[2 * c + 1][1]; M[c][3] = F[2 * c + 1][2];
      }
      wg_fence();
#pragma unroll
      for (int c = 0; c < 6; ++c) {
        if (c == 0) mma48<ACC>(Z, F[0], POS);
        else mma48<1>(Z, F[2 * c], (c * 3 + 0) * 4 + POS);
        mma48<1>(Z, F[2 * c + 1], (c * 3 + 1) * 4 + POS);
        mma48<1>(Z, M[c], (c * 3 + 2) * 4 + POS);
      }
      wg_commit();
    };
    auto store_row = [&](uint8_t* p, const uint32_t (&y)[12], int e) {
      st128(p + e * 192 + 16 * t4, y[6 * e + 0], y[6 * e + 1], y[6 * e + 2], y[6 * e + 3]);
      st64(p + e * 192 + 64 + 8 * t4, y[6 * e + 4], y[6 * e + 5]);
    };

    if (wg == 1) asm volatile("bar.sync 1, 256;" ::: "memory");

    mbar_wait(fb, 0);
    quarter(Z3, std::integral_constant<int, 3>{}, std::integral_constant<int, 0>{}, ROW_PITCH);
    __syncwarp();
    if (lane == 0) mbar_arrive(eb);
#pragma unroll
    for (int q = 0; q < 3; ++q) aq[q] += STAGE_BYTES;
    mbar_wait(fb + 8, 0);
    ldsm4(A[0], ld_addr(0)); ldsm4(B[0], ld_addr(0) + ROW_PITCH);
    ldsm4(A[1], ld_addr(1)); ldsm4(B[1], ld_addr(1) + ROW_PITCH);
#pragma unroll
    for (int i = 0; i < 4; ++i) { S[0][i] = hadd2(A[0][i], B[0][i]); D[0][i] = hsub2(A[0][i], B[0][i]); }
#pragma unroll
    for (int i = 0; i < 2; ++i) { MA[0][i] = mov32(A[0][1 + i]); MB[0][i] = mov32(B[0][1 + i]); MS[0][i] = mov32(S[0][1 + i]); MD[0][i] = mov32(D[0][1 + i]); }
    wg_wait<0>();
#pragma unroll
    for (int i = 0; i < 24; ++i) {
      Z0[i] = 0.f;
      Z1[i] = Z3[i] + b2[(i >> 2) * 2 + (i & 1)];
      Z2[i] = -Z3[i];
    }
#pragma unroll
    for (int i = 0; i < 12; ++i) { yo[i] = 0; ye[i] = 0; }

    int32_t stage_delta = -STAGE_BYTES;
    for (int t = 0; t < NB; ++t) {
      const int cur = (t + 1) & 1;
#pragma unroll
      for (int s = 0; s < 18; ++s) {
        const int c = s / 3, ty = s % 3;
        const int d0 = s * 4;
        wg_fence();
        if (ty < 2) {
          const int cg = 2 * c + ty;
          mma48<1>(Z0, A[cg], d0);
          mma48<1>(Z1, S[cg], d0 + 1);
          mma48<1>(Z2, D[cg], d0 + 2);
          if (s == 0) mma48<0>(Z3, B[cg], d0 + 3);
          else mma48<1>(Z3, B[cg], d0 + 3);
        } else {
          mma48<1>(Z0, MA[c], d0);
          mma48<1>(Z1, MS[c], d0 + 1);
          mma48<1>(Z2, MD[c], d0 + 2);
          mma48<1>(Z3, MB[c], d0 + 3);
        }
        wg_commit();
        if (ty == 0) {
          const int cg = 2 * c + 1;
#pragma unroll
          for (int i = 0; i < 4; ++i) { S[cg][i] = hadd2(A[cg][i], B[cg][i]); D[cg][i] = hsub2(A[cg][i], B[cg][i]); }
#pragma unroll
          for (int i = 0; i < 2; ++i) { MA[c][2 + i] = mov32(A[cg][1 + i]); MB[c][2 + i] = mov32(B[cg][1 + i]); MS[c][2 + i] = mov32(S[cg][1 + i]); MD[c][2 + i] = mov32(D[cg][1 + i]); }
          if (c == 5) {
            __syncwarp();
            if (lane == 0) mbar_arrive(eb + 8 * cur);
#pragma unroll
            for (int q = 0; q < 3; ++q) aq[q] += stage_delta;
            stage_delta = -stage_delta;
          }
        } else if (ty == 1) {
          const int cg = 2 * c + 2;
          if (c == 5) mbar_wait(fb + 8 * (cur ^ 1), ((t + 2) >> 1) & 1);
          ldsm4(A[cg], ld_addr(cg % 12)); ldsm4(B[cg], ld_addr(cg % 12) + ROW_PITCH);
        } else {
          const int cg = 2 * c + 2;
          ldsm4(A[cg + 1], ld_addr((cg + 1) % 12)); ldsm4(B[cg + 1], ld_addr((cg + 1) % 12) + ROW_PITCH);
#pragma unroll
          for (int i = 0; i < 4; ++i) { S[cg][i] = hadd2(A[cg][i], B[cg][i]); D[cg][i] = hsub2(A[cg][i], B[cg][i]); }
#pragma unroll
          for (int i = 0; i < 2; ++i) { MA[c + 1][i] = mov32(A[cg][1 + i]); MB[c + 1][i] = mov32(B[cg][1 + i]); MS[c + 1][i] = mov32(S[cg][1 + i]); MD[c + 1][i] = mov32(D[cg][1 + i]); }
        }
        if (s == 1 && t >= 2) store_row(optr - 2 * OROW, yo, 0);
        if (s == 2 && t >= 2) store_row(optr - 2 * OROW, yo, 1);
        if (s == 3 && t >= 1) store_row(optr - OROW, ye, 0);
        if (s == 4 && t >= 1) store_row(optr - OROW, ye, 1);
        if (s == 4 && t == 0 && wg == 0) asm volatile("bar.arrive 1, 256;" ::: "memory");
        if (s < 17) wg_wait<1>(); else wg_wait<0>();
      }
#pragma unroll
      for (int j = 0; j < 6; ++j)
#pragma unroll
        for (int e = 0; e < 2; ++e) {
          float ev[2];
          yo[6 * e + j] = pack_bf16(Z0[4 * j + 2 * e], Z0[4 * j + 2 * e + 1]);
#pragma unroll
          for (int k = 0; k < 2; ++k) {
            const int i = 4 * j + 2 * e + k;
            const float sm = Z1[i] + Z2[i], df = Z1[i] - Z2[i];
            const float p = fmaf(0.5f, sm, -Z0[i]);
            ev[k] = fmaf(0.5f, df, -Z3[i]);
            Z0[i] = p;
            Z1[i] = (p + b2[2 * j + k]) + Z3[i];
            Z2[i] = p - Z3[i];
          }
          ye[6 * e + j] = pack_bf16(ev[0], ev[1]);
        }
      optr += 2 * OROW;
#pragma unroll
      for (int i = 0; i < 4; ++i) {
        A[0][i] = A[12][i]; B[0][i] = B[12][i]; S[0][i] = S[12][i]; D[0][i] = D[12][i];
        A[1][i] = A[13][i]; B[1][i] = B[13][i];
      }
#pragma unroll
      for (int i = 0; i < 2; ++i) { MA[0][i] = MA[6][i]; MB[0][i] = MB[6][i]; MS[0][i] = MS[6][i]; MD[0][i] = MD[6][i]; }
    }
    quarter(Z0, std::integral_constant<int, 0>{}, std::integral_constant<int, 1>{}, 0);
    store_row(optr - 2 * OROW, yo, 0);
    store_row(optr - 2 * OROW, yo, 1);
    store_row(optr - OROW, ye, 0);
    store_row(optr - OROW, ye, 1);
    wg_wait<0>();
#pragma unroll
    for (int j = 0; j < 6; ++j)
#pragma unroll
      for (int e = 0; e < 2; ++e) yo[6 * e + j] = pack_bf16(Z0[4 * j + 2 * e], Z0[4 * j + 2 * e + 1]);
    store_row(optr, yo, 0);
    store_row(optr, yo, 1);
  }
}

typedef CUresult (*EncodeTiledFn)(CUtensorMap*, CUtensorMapDataType, cuuint32_t, void*, const cuuint64_t*,
                                  const cuuint64_t*, const cuuint32_t*, const cuuint32_t*, CUtensorMapInterleave,
                                  CUtensorMapSwizzle, CUtensorMapL2promotion, CUtensorMapFloatOOBfill);

}

extern "C" void kernel_launch(void* const* d_in, const int* in_sizes, int n_in, void* d_out, int out_size) {
  (void)in_sizes; (void)n_in; (void)out_size;
  static EncodeTiledFn encode = nullptr;
  if (!encode) {
    void* fn = nullptr;
    cudaDriverEntryPointQueryResult qr;
    cudaGetDriverEntryPoint("cuTensorMapEncodeTiled", &fn, cudaEnableDefault, &qr);
    encode = (EncodeTiledFn)fn;
    cudaFuncSetAttribute(conv3x3_kernel, cudaFuncAttributeMaxDynamicSharedMemorySize, SMEM_BYTES);
  }
  CUtensorMap xmap;
  const cuuint64_t dims[3] = {64, (cuuint64_t)(IMG_W * CH * 2 / 128), (cuuint64_t)IMG_H};
  const cuuint64_t strides[2] = {128, (cuuint64_t)IMG_W * CH * 2};
  const cuuint32_t box[3] = {64, ROW_LINES, 1};
  const cuuint32_t estr[3] = {1, 1, 1};
  encode(&xmap, CU_TENSOR_MAP_DATA_TYPE_BFLOAT16, 3, d_in[0], dims, strides, box, estr, CU_TENSOR_MAP_INTERLEAVE_NONE,
         CU_TENSOR_MAP_SWIZZLE_128B, CU_TENSOR_MAP_L2_PROMOTION_L2_256B, CU_TENSOR_MAP_FLOAT_OOB_FILL_NONE);
  conv3x3_kernel<<<128, NUM_THREADS, SMEM_BYTES, cudaStreamPerThread>>>(
      xmap, (const __nv_bfloat16*)d_in[1], (const __nv_bfloat16*)d_in[2], (__nv_bfloat16*)d_out);
}
```

```cpp
#include <cuda_runtime.h>
#include <cuda_bf16.h>
#include <cuda.h>
#include <stdint.h>
#include <type_traits>

#define DEVI __device__ __forceinline__
#define LDA 3
#define PACE_S0 8
#define NPACE 1
#define ST_R0 0
#define PRE0 2
#define PRE1 1
#define PRE2 0
#define NBRK 2
#define NCH 12

namespace {

constexpr int IMG_H = 512, IMG_W = 512, CH = 96;
constexpr int ROW_LINES = 100;
constexpr int ROW_TX = ROW_LINES * 128;
constexpr int ROW_PITCH = 13312;
constexpr int STAGE_BYTES = 2 * ROW_PITCH;
constexpr int RING_BYTES = 2 * STAGE_BYTES;
constexpr int W_RAW = 3 * 96 * 192;
constexpr int W_OFF = RING_BYTES + W_RAW;
constexpr int W_SLOT = 96 * 96;
constexpr int W_KW = 4 * W_SLOT;
constexpr int W_BYTES = 3 * W_KW;
constexpr int BAR_OFF = W_OFF + W_BYTES;
constexpr int SMEM_BYTES = BAR_OFF + 128 + 6144;
constexpr uint32_t SMEM_BASE = 1024;
constexpr int NUM_THREADS = 384;
constexpr uint64_t WDESC = (uint64_t)((SMEM_BASE + W_OFF) >> 4) | ((uint64_t)(128 >> 4) << 32);

__host__ __device__ constexpr int w_slot(int pos) { return pos == 0 ? 2 : pos == 1 ? 1 : pos == 2 ? 3 : 0; }
__host__ __device__ constexpr uint32_t d_outer(int cg, int pos) { return (uint32_t)(((w_slot(pos) * W_SLOT + cg * 768) >> 4) | (((2 * W_KW) >> 4) << 16)); }
__host__ __device__ constexpr uint32_t d_mid(int c, int pos) { return (uint32_t)(((W_KW + w_slot(pos) * W_SLOT + c * 1536) >> 4) | ((768 >> 4) << 16)); }

DEVI uint32_t smem_u32(const void* p) { return (uint32_t)__cvta_generic_to_shared(p); }
DEVI void wg_fence() { asm volatile("wgmma.fence.sync.aligned;" ::: "memory"); }
DEVI void wg_commit() { asm volatile("wgmma.commit_group.sync.aligned;" ::: "memory"); }
template <int N> DEVI void wg_wait() { asm volatile("wgmma.wait_group.sync.aligned %0;" ::"n"(N) : "memory"); }

DEVI void ldsm4(uint32_t (&r)[4], uint32_t addr) {
  asm volatile("ldmatrix.sync.aligned.m8n8.x4.shared.b16 {%0,%1,%2,%3}, [%4];"
               : "=r"(r[0]), "=r"(r[1]), "=r"(r[2]), "=r"(r[3]) : "r"(addr) : "memory");
}
DEVI void stsm4(uint32_t addr, uint32_t r0, uint32_t r1, uint32_t r2, uint32_t r3) {
  asm volatile("stmatrix.sync.aligned.m8n8.x4.shared.b16 [%0], {%1,%2,%3,%4};"
               ::"r"(addr), "r"(r0), "r"(r1), "r"(r2), "r"(r3) : "memory");
}
DEVI uint32_t hadd2(uint32_t a, uint32_t b) { uint32_t r; asm volatile("add.rn.bf16x2 %0, %1, %2;" : "=r"(r) : "r"(a), "r"(b)); return r; }
DEVI uint32_t hsub2(uint32_t a, uint32_t b) { uint32_t r; asm volatile("sub.rn.bf16x2 %0, %1, %2;" : "=r"(r) : "r"(a), "r"(b)); return r; }
DEVI uint32_t or32(uint32_t a, uint32_t z) { uint32_t r; asm volatile("or.b32 %0, %1, %2;" : "=r"(r) : "r"(a), "r"(z)); return r; }
DEVI uint32_t pack_bf16(float lo, float hi) { uint32_t r; asm("cvt.rn.bf16x2.f32 %0, %1, %2;" : "=r"(r) : "f"(hi), "f"(lo)); return r; }
DEVI float bf_lo(uint32_t v) { return __uint_as_float(v << 16); }
DEVI float bf_hi(uint32_t v) { return __uint_as_float(v & 0xffff0000u); }

DEVI void mbar_init(uint32_t bar, uint32_t cnt) { asm volatile("mbarrier.init.shared::cta.b64 [%0], %1;" ::"r"(bar), "r"(cnt) : "memory"); }
DEVI void mbar_arrive(uint32_t bar) { asm volatile("mbarrier.arrive.shared::cta.b64 _, [%0];" ::"r"(bar) : "memory"); }
DEVI void mbar_expect_tx(uint32_t bar, uint32_t tx) { asm volatile("mbarrier.arrive.expect_tx.shared::cta.b64 _, [%0], %1;" ::"r"(bar), "r"(tx) : "memory"); }
DEVI void mbar_wait(uint32_t bar, uint32_t parity) {
  asm volatile(
      "{\n.reg .pred p;\n.reg .u32 c;\n"
      "mbarrier.try_wait.parity.shared::cta.b64 p, [%0], %1;\n"
      "@p bra.uni DONE;\n"
      "mov.u32 c, 0;\n"
      "SPIN:\n"
      "mbarrier.try_wait.parity.shared::cta.b64 p, [%0], %1;\n"
      "@p bra.uni DONE;\n"
      "add.u32 c, c, 1;\n"
      "setp.lt.u32 p, c, 0x400000;\n"
      "@p bra.uni SPIN;\n"
      "DONE:\n}\n" ::"r"(bar), "r"(parity) : "memory");
}
DEVI void tma3(uint32_t dst, const CUtensorMap* map, int c0, int c1, int c2, uint32_t bar) {
  asm volatile("cp.async.bulk.tensor.3d.shared::cluster.global.mbarrier::complete_tx::bytes [%0], [%1, {%3, %4, %5}], [%2];"
               ::"r"(dst), "l"(map), "r"(bar), "r"(c0), "r"(c1), "r"(c2) : "memory");
}
#define ST_OP ""
#define L2P CU_TENSOR_MAP_L2_PROMOTION_L2_256B
DEVI void bulk_load(uint32_t dst, const void* src, uint32_t bytes, uint32_t bar) {
  asm volatile("cp.async.bulk.shared::cluster.global.mbarrier::complete_tx::bytes [%0], [%1], %2, [%3];"
               ::"r"(dst), "l"(src), "r"(bytes), "r"(bar) : "memory");
}

template <int ACC>
DEVI void mma48(float (&d)[24], const uint32_t (&a)[4], uint64_t dbase, uint32_t doff) {
  const uint64_t desc = dbase + (uint64_t)doff;
  asm volatile(
      "wgmma.mma_async.sync.aligned.m64n48k16.f32.bf16.bf16 "
      "{%0,%1,%2,%3,%4,%5,%6,%7,%8,%9,%10,%11,%12,%13,%14,%15,%16,%17,%18,%19,%20,%21,%22,%23}, "
      "{%24,%25,%26,%27}, %28, %29, 1, 1, 1;\n"
      : "+f"(d[0]), "+f"(d[1]), "+f"(d[2]), "+f"(d[3]), "+f"(d[4]), "+f"(d[5]), "+f"(d[6]), "+f"(d[7]),
        "+f"(d[8]), "+f"(d[9]), "+f"(d[10]), "+f"(d[11]), "+f"(d[12]), "+f"(d[13]), "+f"(d[14]), "+f"(d[15]),
        "+f"(d[16]), "+f"(d[17]), "+f"(d[18]), "+f"(d[19]), "+f"(d[20]), "+f"(d[21]), "+f"(d[22]), "+f"(d[23])
      : "r"(a[0]), "r"(a[1]), "r"(a[2]), "r"(a[3]), "l"(desc), "n"(ACC));
}
DEVI void sched_break(uint32_t z) {
  asm volatile("{\n.reg .pred p;\n.reg .u32 c;\nsetp.eq.u32 p, %0, 0;\n@p bra.uni SKIP;\nmov.u32 c, %0;\nBRK:\nnanosleep.u32 c;\nshr.u32 c, c, 1;\nsetp.ne.u32 p, c, 0;\n@p bra.uni BRK;\nSKIP:\n}\n" ::"r"(z) : "memory");
}
DEVI void pin(float (&d)[24]) {
#pragma unroll
  for (int i = 0; i < 24; ++i) asm volatile("" : "+f"(d[i]) :: "memory");
}

template <int OFF>
DEVI void st128(uint64_t p, int on, uint32_t a, uint32_t b, uint32_t c, uint32_t d) {
  asm volatile("{\n.reg .pred p;\nsetp.gt.s32 p, %5, 0;\n@p st.global" ST_OP ".v4.b32 [%0+%6], {%1,%2,%3,%4};\n}\n"
               ::"l"(p), "r"(a), "r"(b), "r"(c), "r"(d), "r"(on), "n"(OFF) : "memory");
}
template <int OFF>
DEVI void st64(uint64_t p, int on, uint32_t a, uint32_t b) {
  asm volatile("{\n.reg .pred p;\nsetp.gt.s32 p, %3, 0;\n@p st.global" ST_OP ".v2.b32 [%0+%4], {%1,%2};\n}\n"
               ::"l"(p), "r"(a), "r"(b), "r"(on), "n"(OFF) : "memory");
}

__global__ void __launch_bounds__(NUM_THREADS, 1)
conv3x3_kernel(const __grid_constant__ CUtensorMap xmap, const uint8_t* __restrict__ wgt,
               const __nv_bfloat16* __restrict__ bias, __nv_bfloat16* __restrict__ out, uint32_t zero, uint32_t zero2) {
  extern __shared__ __align__(1024) uint8_t smem_raw[];
  const uint32_t sbase = smem_u32(smem_raw);
  if ((sbase & 0xFFFFFFu) != SMEM_BASE) __trap();
  const uint32_t bars = sbase + BAR_OFF;
  const int tid = threadIdx.x, warp = __shfl_sync(0xffffffffu, tid >> 5, 0), lane = tid & 31;
  const int half = blockIdx.x & 1, pair = blockIdx.x >> 1;
  constexpr int NB = 16;
  const int line0 = (pair & 7) * 96 - 2, seg0 = (pair >> 3) * (4 * NB);
  if (tid == 0) {
#pragma unroll
    for (int kw = 0; kw < 3; ++kw) mbar_init(bars + 64 + 8 * kw, 1);
    asm volatile("fence.proxy.async.shared::cta;" ::: "memory");
#pragma unroll
    for (int kw = 0; kw < 3; ++kw) {
      mbar_expect_tx(bars + 64 + 8 * kw, W_RAW);
#pragma unroll
      for (int kh = 0; kh < 3; ++kh)
        bulk_load(sbase + RING_BYTES + ((kw + 1) % 3) * W_RAW + kh * (96 * 192), wgt + (kh * 3 + kw) * (96 * 192), 96 * 192, bars + 64 + 8 * kw);
    }
  } else if (tid == 32) {
#pragma unroll
    for (int i = 0; i < 8; ++i) mbar_init(bars + 8 * i, i < 4 ? 1 : 4);
    asm volatile("fence.proxy.async.shared::cta;" ::: "memory");
    asm volatile("prefetch.tensormap [%0];" ::"l"(&xmap) : "memory");
  } else if (tid >= 64 && tid < 75) {
    const uint32_t off = (blockIdx.x * 11 + tid - 64) * 128;
    if (off < 3 * W_RAW) asm volatile("prefetch.global.L2 [%0];" ::"l"(wgt + off));
  }
  const uint4 bias_v = __ldg(reinterpret_cast<const uint4*>(bias + half * 48 + 8 * (lane & 3)));
  const uint2 bias_u = __ldg(reinterpret_cast<const uint2*>(bias + half * 48 + 32 + 4 * (lane & 3)));
  __syncthreads();
  if (tid == 32) {
    mbar_expect_tx(bars, ROW_TX);
    tma3(sbase + ROW_PITCH, &xmap, 0, line0, seg0 - 1, bars);
    mbar_expect_tx(bars + 16, ROW_TX);
    tma3(sbase, &xmap, 0, line0, seg0 + 4 * NB, bars + 16);
    mbar_expect_tx(bars + 8, 2 * ROW_TX);
    tma3(sbase + STAGE_BYTES, &xmap, 0, line0, seg0, bars + 8);
    tma3(sbase + STAGE_BYTES + ROW_PITCH, &xmap, 0, line0, seg0 + 1, bars + 8);
  }
  __syncwarp();

  {
    const int p = 16 * (warp & 3) + 2 * (lane & 7) - 1 + (lane >> 3);
    const uint32_t off = 192 * p + 256 + 64 * (warp >> 2), a0 = sbase + (off ^ (((off >> 7) & 7) << 4));
    asm volatile("st.shared.v4.b32 [%0], {%1,%2,%3,%4};" ::"r"(bars + 128 + tid * 16), "r"(a0), "r"(a0 ^ 16), "r"(a0 ^ 32), "r"(a0 ^ 48) : "memory");
  }
  {
    const int g = lane >> 2, t4 = lane & 3;
    uint32_t blk = sbase + W_OFF + warp * 768;
#pragma unroll 1
    for (int kw = 0; kw < 3; ++kw, blk += W_KW) {
      const uint32_t src = sbase + RING_BYTES + (kw == 2 ? 0 : kw + 1) * W_RAW + (warp * 8 + g) * 192 + half * 96;
      mbar_wait(bars + 64 + 8 * kw, 0);
      uint32_t raw[3][6];
#pragma unroll
      for (int kh = 0; kh < 3; ++kh) {
        asm volatile("ld.shared.v4.b32 {%0,%1,%2,%3}, [%4];" : "=r"(raw[kh][0]), "=r"(raw[kh][1]), "=r"(raw[kh][2]), "=r"(raw[kh][3])
                     : "r"(src + kh * (96 * 192) + 16 * t4) : "memory");
        asm volatile("ld.shared.v2.b32 {%0,%1}, [%2];" : "=r"(raw[kh][4]), "=r"(raw[kh][5])
                     : "r"(src + kh * (96 * 192) + 64 + 8 * t4) : "memory");
      }
      if (kw < 2) __syncthreads();
      const uint32_t d4 = blk + lane * 16;
      const uint32_t d2 = blk + 512 + (lane & 15) * 16 + (lane >> 4) * (2 * W_SLOT);
      stsm4(d4, raw[0][0], raw[0][1], raw[0][2], raw[0][3]);
      stsm4(d4 + 2 * W_SLOT, raw[2][0], raw[2][1], raw[2][2], raw[2][3]);
      stsm4(d2, raw[0][4], raw[0][5], raw[2][4], raw[2][5]);
      uint32_t u1[6], u2[6];
#pragma unroll
      for (int j = 0; j < 6; ++j) {
        const float tl = bf_lo(raw[0][j]) + bf_lo(raw[2][j]), th = bf_hi(raw[0][j]) + bf_hi(raw[2][j]);
        const float ml = bf_lo(raw[1][j]), mh = bf_hi(raw[1][j]);
        u1[j] = pack_bf16(tl + ml, th + mh);
        u2[j] = pack_bf16(tl - ml, th - mh);
      }
      stsm4(d4 + W_SLOT, u1[0], u1[1], u1[2], u1[3]);
      stsm4(d4 + 3 * W_SLOT, u2[0], u2[1], u2[2], u2[3]);
      stsm4(d2 + W_SLOT, u1[4], u1[5], u2[4], u2[5]);
    }
    asm volatile("fence.proxy.async.shared::cta;" ::: "memory");
  }
  __syncthreads();
  if (warp >= 8) {
    asm volatile("setmaxnreg.dec.sync.aligned.u32 24;");
    if (warp < 10 && lane == 0) {
      const int wg = warp - 8, dir = 1 - 2 * wg;
      const uint32_t ring = sbase + wg * RING_BYTES, fb = bars + wg * 16, eb = fb + 32;
      if (wg == 0) mbar_wait(eb + 16, 0);
#pragma unroll 1
      for (int i = 2 - wg; i <= NB; ++i) {
        const int s = i & 1;
        mbar_wait(eb + 8 * s, ((i >> 1) - 1) & 1);
        const int y = seg0 + wg * (4 * NB - 1) + dir * 2 * (i - 1);
        const uint32_t dst = ring + s * STAGE_BYTES;
        mbar_expect_tx(fb + 8 * s, 2 * ROW_TX);
        tma3(dst, &xmap, 0, line0, y, fb + 8 * s);
        tma3(dst + ROW_PITCH, &xmap, 0, line0, y + dir, fb + 8 * s);
      }
    } else if (warp >= 10) {
      const int wg = warp - 10;
#pragma unroll 1
      for (int i = 1; i <= NB; ++i) {
        mbar_wait(bars + wg * 16 + 8 * (i & 1), (i >> 1) & 1);
        asm volatile("bar.sync %0, 288;" ::"r"(2 - wg) : "memory");
      }
    }
  } else {
    asm volatile("setmaxnreg.inc.sync.aligned.u32 240;");
    const int wg = warp >> 2, w = warp & 3;
    const uint32_t fb = bars + wg * 16, eb = fb + 32;
    const int g = lane >> 2, t4 = lane & 3;

    uint32_t la[12];
#pragma unroll
    for (int q = 0; q < 3; ++q)
      asm volatile("ld.shared.v4.b32 {%0,%1,%2,%3}, [%4];" : "=r"(la[4 * q]), "=r"(la[4 * q + 1]), "=r"(la[4 * q + 2]), "=r"(la[4 * q + 3])
                   : "r"(bars + 128 + q * 2048 + (tid & 127) * 16) : "memory");
    uint32_t soff = wg * RING_BYTES;
    float b2[12];
    {
      const uint32_t r[6] = {bias_v.x, bias_v.y, bias_v.z, bias_v.w, bias_u.x, bias_u.y};
#pragma unroll
      for (int j = 0; j < 6; ++j) { b2[2 * j] = 2.f * bf_lo(r[j]); b2[2 * j + 1] = 2.f * bf_hi(r[j]); }
    }
    constexpr int OROW = IMG_W * CH * 2;
    const int orow = wg ? -OROW : OROW;
    uint64_t op16 = (uint64_t)__cvta_generic_to_global(out) + (ptrdiff_t)(seg0 + wg * (4 * NB - 1)) * OROW - 3 * (ptrdiff_t)orow
                    + ((pair & 7) * 64 + 16 * w + 2 * g) * (CH * 2) + half * 96 + 16 * t4;
    uint64_t op8 = op16 + 64 - 8 * t4, oq16 = op16 + orow, oq8 = op8 + orow;
    const uint64_t dswap = wg ? (uint64_t)((2 * W_SLOT) >> 4) : 0;
    const uint32_t bar_tx0 = 1 + wg, bar_rx0 = 2 - wg;

    constexpr int NAB = LDA + 2;
    float Z0[24], Z1[24], Z2[24], Z3[24];
    uint32_t A[NAB][4], B[NAB][4], S[3][4], D[3][4], MP[3][4], MQ[3][4];
    auto store = [&](const uint32_t (&y)[12], int n, int on, uint64_t p16, uint64_t p8) {
      if (n == 0) st128<0>(p16, on, y[0], y[1], y[2], y[3]);
      if (n == 1) st128<192>(p16, on, y[6], y[7], y[8], y[9]);
      if (n == 2) st64<0>(p8, on, y[4], y[5]);
      if (n == 3) st64<192>(p8, on, y[10], y[11]);
    };
    auto ld_addr = [&](int cg) { return la[cg] + soff; };
    auto load = [&](int cg) { ldsm4(A[cg % NAB], ld_addr(cg)); ldsm4(B[cg % NAB], ld_addr(cg) + ROW_PITCH); };
    auto prep = [&](int r) {
#pragma unroll
      for (int i = 0; i < 4; ++i) {
        if (r < 12) S[r % 3][i] = hadd2(A[r % NAB][i], B[r % NAB][i]);
        if (r > 0) {
          const int src = ((r - 1) & ~1) + (i >> 1);
          MP[r % 3][i] = or32((r & 1) ? A[src % NAB][1 + (i & 1)] : S[src % 3][1 + (i & 1)], zero2);
        }
        if (r < 12) D[r % 3][i] = hsub2(A[r % NAB][i], B[r % NAB][i]);
        if (r > 0) {
          const int src = ((r - 1) & ~1) + (i >> 1);
          MQ[r % 3][i] = or32((r & 1) ? B[src % NAB][1 + (i & 1)] : D[src % 3][1 + (i & 1)], zero2);
        }
      }
    };
    if (wg == 1) asm volatile("bar.arrive 2, 288;" ::: "memory");
    mbar_wait(fb, 0);
    {
      uint32_t F[12][4], M[6][4];
      const uint64_t d3 = WDESC + dswap + zero2;
#pragma unroll
      for (int cg = 0; cg < 12; ++cg) ldsm4(F[cg], la[cg] + (wg ? 0 : ROW_PITCH));
#pragma unroll
      for (int c = 0; c < 6; ++c) {
        M[c][0] = F[2 * c][1]; M[c][1] = F[2 * c][2]; M[c][2] = F[2 * c + 1][1]; M[c][3] = F[2 * c + 1][2];
      }
      wg_fence();
#pragma unroll
      for (int c = 0; c < 6; ++c) {
        if (c == 0) mma48<0>(Z3, F[0], d3, d_outer(0, 3));
        else mma48<1>(Z3, F[2 * c], d3, d_outer(2 * c, 3));
        mma48<1>(Z3, F[2 * c + 1], d3, d_outer(2 * c + 1, 3));
        mma48<1>(Z3, M[c], d3, d_mid(c, 3));
      }
      wg_commit();
    }
    __syncwarp();
    if (lane == 0) mbar_arrive(eb);
    wg_wait<0>();
    pin(Z3);
#pragma unroll
    for (int i = 0; i < 24; ++i) {
      Z0[i] = 0.f;
      Z1[i] = Z3[i] + b2[(i >> 2) * 2 + (i & 1)];
      Z2[i] = -Z3[i];
    }
#pragma unroll
    for (int i = 0; i < 4; ++i) { A[11 % NAB][i] = 0; B[11 % NAB][i] = 0; S[11 % 3][i] = 0; D[11 % 3][i] = 0; MP[12 % 3][i] = 0; MQ[12 % 3][i] = 0; }
    uint32_t ebar = eb;
    for (int t = 0;; ++t) {
      uint32_t yo[12], ye[12];
#pragma unroll
      for (int i = 0; i < 4; ++i) {
        yo[i] = A[11 % NAB][i]; yo[6 + i] = B[11 % NAB][i]; ye[i] = S[11 % 3][i]; ye[6 + i] = D[11 % 3][i];
        yo[4 + (i & 1) + 6 * (i >> 1)] = MP[12 % 3][i]; ye[4 + (i & 1) + 6 * (i >> 1)] = MQ[12 % 3][i];
      }
#pragma unroll
      for (int k = 0; k <= NCH; ++k) {
        if (k == NCH - PRE0) {
          soff = wg * RING_BYTES + ((t + 1) & 1) * STAGE_BYTES; ebar ^= 8;
          if (t < NB) asm volatile("bar.sync %0, 288;" ::"r"(bar_rx0) : "memory");
          load(0);
        }
        if (k == NCH - PRE1) load(1);
        if (LDA > 2 && PRE2 > 0 && k == NCH - PRE2) load(2);
        if (k < NCH && t > (int)((k & 1) ? zero : zero2)) {
          float ev[2];
#pragma unroll
          for (int n = k * 24 / NCH; n < (k + 1) * 24 / NCH; ++n) {
            const int e = n / 12, j = (n % 12) >> 1, u = n & 1, i = 4 * j + 2 * e + u;
            if (u == 0) yo[6 * e + j] = pack_bf16(Z0[i], Z0[i + 1]);
            const float sm = Z1[i] + Z2[i], df = Z1[i] - Z2[i];
            const float p = fmaf(0.5f, sm, -Z0[i]);
            ev[u] = fmaf(0.5f, df, -Z3[i]);
            Z0[i] = p;
            Z1[i] = (p + b2[2 * j + u]) + Z3[i];
            Z2[i] = p - Z3[i];
            if (u == 1) ye[6 * e + j] = pack_bf16(ev[0], ev[1]);
            if (n % 12 == 6) store(yo, e, t - 1, op16, op8);
            if (n % 12 == 8) store(ye, e, 1, oq16, oq8);
            if (n % 12 == 10) store(yo, 2 + e, t - 1, op16, op8);
            if (n % 12 == 11) store(ye, 2 + e, 1, oq16, oq8);
            if (n == 0) { op16 += 2 * orow; op8 += 2 * orow; }
            if (n == 2) { oq16 += 2 * orow; oq8 += 2 * orow; }
          }
        }
      }
      if (t == NB) break;
      if (LDA > 2 && PRE2 == 0) load(2);
      prep(0);
      const uint64_t dbase = WDESC + (uint64_t)(t & zero), db0 = dbase - dswap, db3 = dbase + dswap;
#pragma unroll
      for (int r = 0; r < 13; ++r) {
        if (r == 0) wg_fence();
        if (r < 12) {
          mma48<1>(Z0, A[r % NAB], db0, d_outer(r, 0));
          mma48<1>(Z1, S[r % 3], dbase, d_outer(r, 1));
          mma48<1>(Z2, D[r % 3], dbase, d_outer(r, 2));
          if (r == 0) mma48<0>(Z3, B[r % NAB], db3, d_outer(r, 3));
          else mma48<1>(Z3, B[r % NAB], db3, d_outer(r, 3));
        }
        if (r > 0) {
          const int c = (r - 1) >> 1;
          if (r & 1) { mma48<1>(Z0, MP[r % 3], db0, d_mid(c, 0)); mma48<1>(Z3, MQ[r % 3], db3, d_mid(c, 3)); }
          else       { mma48<1>(Z1, MP[r % 3], dbase, d_mid(c, 1)); mma48<1>(Z2, MQ[r % 3], dbase, d_mid(c, 2)); }
        }
        wg_commit();
        if (r == PACE_S0 && t + wg < NB) asm volatile("bar.arrive %0, 288;" ::"r"(bar_tx0) : "memory");
        if (r + LDA < 12) load(r + LDA);
        if (r < 12) prep(r + 1);
        if (r == 11) {
          __syncwarp();
          if (lane == 0) mbar_arrive(ebar);
        }
        if (r < 12) { if (r < NBRK) sched_break(zero); wg_fence(); wg_wait<1>(); } else wg_wait<0>();
      }
      pin(Z0); pin(Z1); pin(Z2); pin(Z3);
    }
    {
      const uint32_t xch = sbase + STAGE_BYTES + (tid & 127) * 16;
      uint32_t y2[12], y3[12];
      if (wg == 0) {
#pragma unroll
        for (int j = 0; j < 6; ++j) {
          asm volatile("st.shared.v4.f32 [%4], {%0,%1,%2,%3};"
                       ::"f"(Z0[4 * j]), "f"(Z0[4 * j + 1]), "f"(Z0[4 * j + 2]), "f"(Z0[4 * j + 3]), "r"(xch + j * 4096) : "memory");
          asm volatile("st.shared.v4.f32 [%4], {%0,%1,%2,%3};"
                       ::"f"(Z3[4 * j]), "f"(Z3[4 * j + 1]), "f"(Z3[4 * j + 2]), "f"(Z3[4 * j + 3]), "r"(xch + j * 4096 + 2048) : "memory");
        }
        asm volatile("bar.arrive 3, 256;" ::: "memory");
      } else {
        asm volatile("bar.sync 3, 256;" ::: "memory");
      }
#pragma unroll
      for (int j = 0; j < 6; ++j) {
        asm volatile("{\n.reg .pred p;\nsetp.gt.s32 p, %5, 0;\n@p ld.shared.v4.f32 {%0,%1,%2,%3}, [%4];\n}\n"
                     : "+f"(Z1[4 * j]), "+f"(Z1[4 * j + 1]), "+f"(Z1[4 * j + 2]), "+f"(Z1[4 * j + 3]) : "r"(xch + j * 4096), "r"(wg + zero) : "memory");
        asm volatile("{\n.reg .pred p;\nsetp.gt.s32 p, %5, 0;\n@p ld.shared.v4.f32 {%0,%1,%2,%3}, [%4];\n}\n"
                     : "+f"(Z2[4 * j]), "+f"(Z2[4 * j + 1]), "+f"(Z2[4 * j + 2]), "+f"(Z2[4 * j + 3]) : "r"(xch + j * 4096 + 2048), "r"(wg + zero2) : "memory");
#pragma unroll
        for (int e = 0; e < 2; ++e) {
          const int i = 4 * j + 2 * e;
          y2[6 * e + j] = pack_bf16(Z0[i] + Z2[i], Z0[i + 1] + Z2[i + 1]);
          y3[6 * e + j] = pack_bf16(Z3[i] + Z1[i], Z3[i + 1] + Z1[i + 1]);
        }
      }
#pragma unroll
      for (int n = 0; n < 4; ++n) {
        store(y2, n, wg + zero, op16 + 2 * orow, op8 + 2 * orow);
        store(y3, n, wg + zero2, oq16 + 2 * orow, oq8 + 2 * orow);
      }
    }
  }
}

typedef CUresult (*EncodeTiledFn)(CUtensorMap*, CUtensorMapDataType, cuuint32_t, void*, const cuuint64_t*,
                                  const cuuint64_t*, const cuuint32_t*, const cuuint32_t*, CUtensorMapInterleave,
                                  CUtensorMapSwizzle, CUtensorMapL2promotion, CUtensorMapFloatOOBfill);

}

extern "C" void kernel_launch(void* const* d_in, const int* in_sizes, int n_in, void* d_out, int out_size) {
  (void)in_sizes; (void)n_in; (void)out_size;
  static EncodeTiledFn encode = nullptr;
  if (!encode) {
    void* fn = nullptr;
    cudaDriverEntryPointQueryResult qr;
    cudaGetDriverEntryPoint("cuTensorMapEncodeTiled", &fn, cudaEnableDefault, &qr);
    encode = (EncodeTiledFn)fn;
    cudaFuncSetAttribute(conv3x3_kernel, cudaFuncAttributeMaxDynamicSharedMemorySize, SMEM_BYTES);
  }
  const cuuint32_t estr[3] = {1, 1, 1};
  CUtensorMap xmap;
  {
    const cuuint64_t dims[3] = {64, (cuuint64_t)(IMG_W * CH * 2 / 128), (cuuint64_t)IMG_H};
    const cuuint64_t strides[2] = {128, (cuuint64_t)IMG_W * CH * 2};
    const cuuint32_t box[3] = {64, ROW_LINES, 1};
    encode(&xmap, CU_TENSOR_MAP_DATA_TYPE_BFLOAT16, 3, d_in[0], dims, strides, box, estr, CU_TENSOR_MAP_INTERLEAVE_NONE,
           CU_TENSOR_MAP_SWIZZLE_128B, L2P, CU_TENSOR_MAP_FLOAT_OOB_FILL_NONE);
  }
  conv3x3_kernel<<<128, NUM_THREADS, SMEM_BYTES, cudaStreamPerThread>>>(
      xmap, (const uint8_t*)d_in[1], (const __nv_bfloat16*)d_in[2], (__nv_bfloat16*)d_out, 0u, 0u);
}
```

```cpp
#include <cuda_runtime.h>
#include <cuda_bf16.h>
#include <cuda.h>
#include <stdint.h>
#include <type_traits>

#define DEVI __device__ __forceinline__
#define LDA 3
#define PACE_S0 8
#define NPACE 1
#define ST_R0 0
#define PRE0 2
#define PRE1 1
#define PRE2 0
#define SPLIT 0
#define FA 3
#define PFD 2
#define PFS 3
#define DLY0 0
#define DLY1 0
#define HINT 1
#define PAD 0
#define PF1 1
#define TFENCE 1
#define LEADORD 1
#define LG 1
#define SKIP0 1
#define EARLYPF 1
#define NBRK 0
#define NCH 12

namespace {

constexpr int IMG_H = 512, IMG_W = 512, CH = 96;
constexpr int ROW_LINES = 100;
constexpr int ROW_TX = ROW_LINES * 128;
constexpr int ROW_PITCH = 13312;
constexpr int STAGE_BYTES = 2 * ROW_PITCH;
constexpr int RING_BYTES = 2 * STAGE_BYTES;
constexpr int W_RAW = 3 * 96 * 192;
constexpr int W_OFF = RING_BYTES + W_RAW;
constexpr int W_SLOT = 96 * 96;
constexpr int W_KW = 4 * W_SLOT;
constexpr int W_BYTES = 3 * W_KW;
constexpr int BAR_OFF = W_OFF + W_BYTES;
constexpr int SMEM_BYTES = BAR_OFF + 128 + 6144;
constexpr uint32_t SMEM_BASE = 1024;
constexpr int NUM_THREADS = 384;
constexpr uint64_t WDESC = (uint64_t)((SMEM_BASE + W_OFF) >> 4) | ((uint64_t)(128 >> 4) << 32);

__host__ __device__ constexpr int w_slot(int pos) { return pos == 0 ? 2 : pos == 1 ? 1 : pos == 2 ? 3 : 0; }
__host__ __device__ constexpr uint32_t d_outer(int cg, int pos) { return (uint32_t)(((w_slot(pos) * W_SLOT + cg * 768) >> 4) | (((2 * W_KW) >> 4) << 16)); }
__host__ __device__ constexpr uint32_t d_mid(int c, int pos) { return (uint32_t)(((W_KW + w_slot(pos) * W_SLOT + c * 1536) >> 4) | ((768 >> 4) << 16)); }

DEVI uint32_t smem_u32(const void* p) { return (uint32_t)__cvta_generic_to_shared(p); }
DEVI void wg_fence() { asm volatile("wgmma.fence.sync.aligned;" ::: "memory"); }
DEVI void wg_commit() { asm volatile("wgmma.commit_group.sync.aligned;" ::: "memory"); }
template <int N> DEVI void wg_wait() { asm volatile("wgmma.wait_group.sync.aligned %0;" ::"n"(N) : "memory"); }

DEVI void ldsm4(uint32_t (&r)[4], uint32_t addr) {
  asm volatile("ldmatrix.sync.aligned.m8n8.x4.shared.b16 {%0,%1,%2,%3}, [%4];"
               : "=r"(r[0]), "=r"(r[1]), "=r"(r[2]), "=r"(r[3]) : "r"(addr) : "memory");
}
DEVI void stsm4(uint32_t addr, uint32_t r0, uint32_t r1, uint32_t r2, uint32_t r3) {
  asm volatile("stmatrix.sync.aligned.m8n8.x4.shared.b16 [%0], {%1,%2,%3,%4};"
               ::"r"(addr), "r"(r0), "r"(r1), "r"(r2), "r"(r3) : "memory");
}
DEVI uint32_t hadd2(uint32_t a, uint32_t b) { uint32_t r; asm volatile("add.rn.bf16x2 %0, %1, %2;" : "=r"(r) : "r"(a), "r"(b)); return r; }
DEVI uint32_t hsub2(uint32_t a, uint32_t b) { uint32_t r; asm volatile("sub.rn.bf16x2 %0, %1, %2;" : "=r"(r) : "r"(a), "r"(b)); return r; }
DEVI uint32_t or32(uint32_t a, uint32_t z) { uint32_t r; asm volatile("or.b32 %0, %1, %2;" : "=r"(r) : "r"(a), "r"(z)); return r; }
DEVI uint32_t pack_bf16(float lo, float hi) { uint32_t r; asm("cvt.rn.bf16x2.f32 %0, %1, %2;" : "=r"(r) : "f"(hi), "f"(lo)); return r; }
DEVI float fadd(float a, float b) { float r; asm volatile("add.rn.f32 %0, %1, %2;" : "=f"(r) : "f"(a), "f"(b)); return r; }
DEVI float fsub(float a, float b) { float r; asm volatile("sub.rn.f32 %0, %1, %2;" : "=f"(r) : "f"(a), "f"(b)); return r; }
DEVI float fmah(float a, float b) { float r; asm volatile("fma.rn.f32 %0, %1, 0f3F000000, %2;" : "=f"(r) : "f"(a), "f"(-b)); return r; }
DEVI float bf_lo(uint32_t v) { return __uint_as_float(v << 16); }
DEVI float bf_hi(uint32_t v) { return __uint_as_float(v & 0xffff0000u); }

DEVI void mbar_init(uint32_t bar, uint32_t cnt) { asm volatile("mbarrier.init.shared::cta.b64 [%0], %1;" ::"r"(bar), "r"(cnt) : "memory"); }
DEVI void mbar_expect_tx(uint32_t bar, uint32_t tx) { asm volatile("mbarrier.arrive.expect_tx.shared::cta.b64 _, [%0], %1;" ::"r"(bar), "r"(tx) : "memory"); }
DEVI void mbar_wait(uint32_t bar, uint32_t parity) {
  asm volatile(
      "{\n.reg .pred p;\n.reg .u32 c;\n"
      "mbarrier.try_wait.parity.shared::cta.b64 p, [%0], %1;\n"
      "@p bra.uni DONE;\n"
      "mov.u32 c, 0;\n"
      "SPIN:\n"
      "mbarrier.try_wait.parity.shared::cta.b64 p, [%0], %1, 100000;\n"
      "@p bra.uni DONE;\n"
      "add.u32 c, c, 1;\n"
      "setp.lt.u32 p, c, 0x10000;\n"
      "@p bra.uni SPIN;\n"
      "DONE:\n}\n" ::"r"(bar), "r"(parity) : "memory");
}
DEVI void tma3(uint32_t dst, const CUtensorMap* map, int c0, int c1, int c2, uint32_t bar) {
  asm volatile("cp.async.bulk.tensor.3d.shared::cluster.global.mbarrier::complete_tx::bytes [%0], [%1, {%3, %4, %5}], [%2];"
               ::"r"(dst), "l"(map), "r"(bar), "r"(c0), "r"(c1), "r"(c2) : "memory");
}
DEVI void tma3_prefetch(const CUtensorMap* map, int c0, int c1, int c2) {
  asm volatile("cp.async.bulk.prefetch.tensor.3d.L2.global [%0, {%1, %2, %3}];" ::"l"(map), "r"(c0), "r"(c1), "r"(c2) : "memory");
}
DEVI bool elect_one() {
  uint32_t p;
  asm volatile("{\n.reg .pred p;\nelect.sync _|p, 0xffffffff;\nselp.b32 %0, 1, 0, p;\n}\n" : "=r"(p));
  return p != 0;
}
DEVI void bulk_load(uint32_t dst, const void* src, uint32_t bytes, uint32_t bar) {
  asm volatile("cp.async.bulk.shared::cluster.global.mbarrier::complete_tx::bytes [%0], [%1], %2, [%3];"
               ::"r"(dst), "l"(src), "r"(bytes), "r"(bar) : "memory");
}

template <int ACC>
DEVI void mma48(float (&d)[24], const uint32_t (&a)[4], uint64_t dbase, uint32_t doff) {
  const uint64_t desc = dbase + (uint64_t)doff;
  asm volatile(
      "wgmma.mma_async.sync.aligned.m64n48k16.f32.bf16.bf16 "
      "{%0,%1,%2,%3,%4,%5,%6,%7,%8,%9,%10,%11,%12,%13,%14,%15,%16,%17,%18,%19,%20,%21,%22,%23}, "
      "{%24,%25,%26,%27}, %28, %29, 1, 1, 1;\n"
      : "+f"(d[0]), "+f"(d[1]), "+f"(d[2]), "+f"(d[3]), "+f"(d[4]), "+f"(d[5]), "+f"(d[6]), "+f"(d[7]),
        "+f"(d[8]), "+f"(d[9]), "+f"(d[10]), "+f"(d[11]), "+f"(d[12]), "+f"(d[13]), "+f"(d[14]), "+f"(d[15]),
        "+f"(d[16]), "+f"(d[17]), "+f"(d[18]), "+f"(d[19]), "+f"(d[20]), "+f"(d[21]), "+f"(d[22]), "+f"(d[23])
      : "r"(a[0]), "r"(a[1]), "r"(a[2]), "r"(a[3]), "l"(desc), "n"(ACC));
}
DEVI void sched_break(uint32_t z) {
  asm volatile("{\n.reg .pred p;\n.reg .u32 c;\nsetp.eq.u32 p, %0, 0;\n@p bra.uni SKIP;\nmov.u32 c, %0;\nBRK:\nnanosleep.u32 c;\nshr.u32 c, c, 1;\nsetp.ne.u32 p, c, 0;\n@p bra.uni BRK;\nSKIP:\n}\n" ::"r"(z) : "memory");
}
DEVI void pin(float (&d)[24]) {
#pragma unroll
  for (int i = 0; i < 24; ++i) asm volatile("" : "+f"(d[i]) :: "memory");
}

template <int OFF>
DEVI void st128(uint64_t p, int on, uint32_t a, uint32_t b, uint32_t c, uint32_t d) {
  asm volatile("{\n.reg .pred p;\nsetp.gt.s32 p, %5, 0;\n@p st.global.v4.b32 [%0+%6], {%1,%2,%3,%4};\n}\n"
               ::"l"(p), "r"(a), "r"(b), "r"(c), "r"(d), "r"(on), "n"(OFF) : "memory");
}
template <int OFF>
DEVI void st64(uint64_t p, int on, uint32_t a, uint32_t b) {
  asm volatile("{\n.reg .pred p;\nsetp.gt.s32 p, %3, 0;\n@p st.global.v2.b32 [%0+%4], {%1,%2};\n}\n"
               ::"l"(p), "r"(a), "r"(b), "r"(on), "n"(OFF) : "memory");
}

__global__ void __launch_bounds__(NUM_THREADS, 1)
conv3x3_kernel(const __grid_constant__ CUtensorMap xmap, const uint8_t* __restrict__ wgt,
               const __nv_bfloat16* __restrict__ bias, __nv_bfloat16* __restrict__ out, uint32_t zero, uint32_t zero2) {
  extern __shared__ __align__(1024) uint8_t smem_raw[];
  if (threadIdx.x < 11) asm volatile("prefetch.global.L2 [%0];" ::"l"(wgt + min((blockIdx.x * 11 + threadIdx.x) * 128, 3 * W_RAW - 128)));
  const uint32_t sbase = smem_u32(smem_raw);
  const uint32_t bars = sbase + BAR_OFF;
  const int tid = threadIdx.x, warp = __shfl_sync(0xffffffffu, tid >> 5, 0), lane = tid & 31;
  const int half = blockIdx.x & 1, pair = blockIdx.x >> 1;
  constexpr int NB = 16;
  const int off64 = half * 128, off32 = 64 + half * 32;
  const int line0 = (pair & 7) * 96 - 2, seg0 = (pair >> 3) * (4 * NB);

  if (warp == 11) {
    if (elect_one()) {
#pragma unroll
      for (int kw = 0; kw < 3; ++kw) mbar_init(bars + 64 + 8 * kw, 1);
      asm volatile("fence.proxy.async.shared::cta;" ::: "memory");
#pragma unroll
      for (int kw = 0; kw < 3; ++kw) {
        mbar_expect_tx(bars + 64 + 8 * kw, W_RAW);
#pragma unroll
        for (int kh = 0; kh < 3; ++kh)
          bulk_load(sbase + RING_BYTES + ((kw + 1) % 3) * W_RAW + kh * (96 * 192), wgt + (kh * 3 + kw) * (96 * 192), 96 * 192, bars + 64 + 8 * kw);
      }
#pragma unroll
      for (int i = 0; i < 4; ++i) mbar_init(bars + 8 * i, 1);
      asm volatile("fence.proxy.async.shared::cta;" ::: "memory");
      mbar_expect_tx(bars, ROW_TX);
      tma3(sbase + ROW_PITCH, &xmap, 0, line0, seg0 - 1, bars);
      mbar_expect_tx(bars + 16, ROW_TX);
      tma3(sbase, &xmap, 0, line0, seg0 + 4 * NB, bars + 16);
      mbar_expect_tx(bars + 8, 2 * ROW_TX);
      tma3(sbase + STAGE_BYTES, &xmap, 0, line0, seg0, bars + 8);
      tma3(sbase + STAGE_BYTES + ROW_PITCH, &xmap, 0, line0, seg0 + 1, bars + 8);
    }
  }
  if ((sbase & 0xFFFFFFu) != SMEM_BASE) __trap();
  const uint4 bias_v = __ldg(reinterpret_cast<const uint4*>(bias + off64 / 2 + 8 * (lane & 3)));
  const uint2 bias_u = __ldg(reinterpret_cast<const uint2*>(bias + off32 / 2 + 4 * (lane & 3)));
  __syncthreads();
  {
    const int p = 16 * (warp & 3) + 2 * (lane & 7) - 1 + (lane >> 3);
    const uint32_t off = 192 * p + 256 + 64 * (warp >> 2), a0 = sbase + (off ^ (((off >> 7) & 7) << 4));
    asm volatile("st.shared.v4.b32 [%0], {%1,%2,%3,%4};" ::"r"(bars + 128 + tid * 16), "r"(a0), "r"(a0 ^ 16), "r"(a0 ^ 32), "r"(a0 ^ 48) : "memory");
  }
  {
    const int g = lane >> 2, t4 = lane & 3;
    uint32_t blk = sbase + W_OFF + warp * 768;
#pragma unroll 1
    for (int kw = 0; kw < 3; ++kw, blk += W_KW) {
      const uint32_t src = sbase + RING_BYTES + (kw == 2 ? 0 : kw + 1) * W_RAW + (warp * 8 + g) * 192;
      mbar_wait(bars + 64 + 8 * kw, 0);
      uint32_t raw[3][6];
#pragma unroll
      for (int kh = 0; kh < 3; ++kh) {
        asm volatile("ld.shared.v4.b32 {%0,%1,%2,%3}, [%4];" : "=r"(raw[kh][0]), "=r"(raw[kh][1]), "=r"(raw[kh][2]), "=r"(raw[kh][3])
                     : "r"(src + kh * (96 * 192) + off64 + 16 * t4) : "memory");
        asm volatile("ld.shared.v2.b32 {%0,%1}, [%2];" : "=r"(raw[kh][4]), "=r"(raw[kh][5])
                     : "r"(src + kh * (96 * 192) + off32 + 8 * t4) : "memory");
      }
      if (kw < 2) __syncthreads();
      const uint32_t d4 = blk + lane * 16;
      const uint32_t d2 = blk + 512 + (lane & 15) * 16 + (lane >> 4) * (2 * W_SLOT);
      stsm4(d4, raw[0][0], raw[0][1], raw[0][2], raw[0][3]);
      stsm4(d4 + 2 * W_SLOT, raw[2][0], raw[2][1], raw[2][2], raw[2][3]);
      stsm4(d2, raw[0][4], raw[0][5], raw[2][4], raw[2][5]);
      uint32_t u1[6], u2[6];
#pragma unroll
      for (int j = 0; j < 6; ++j) {
        const float tl = bf_lo(raw[0][j]) + bf_lo(raw[2][j]), th = bf_hi(raw[0][j]) + bf_hi(raw[2][j]);
        const float ml = bf_lo(raw[1][j]), mh = bf_hi(raw[1][j]);
        u1[j] = pack_bf16(tl + ml, th + mh);
        u2[j] = pack_bf16(tl - ml, th - mh);
      }
      stsm4(d4 + W_SLOT, u1[0], u1[1], u1[2], u1[3]);
      stsm4(d4 + 3 * W_SLOT, u2[0], u2[1], u2[2], u2[3]);
      stsm4(d2 + W_SLOT, u1[4], u1[5], u2[4], u2[5]);
    }
    asm volatile("fence.proxy.async.shared::cta;" ::: "memory");
  }
  __syncthreads();
  if (warp >= 8) {
    asm volatile("setmaxnreg.dec.sync.aligned.u32 24;");
    if (warp < 10) {
      const int w = warp - 8, o = w ^ 1, dir = 1 - 2 * o;
      const int ybase = seg0 + o * (4 * NB - 1);
      auto fill = [&](int wg, int t, int y, int dy) {
        const uint32_t dst = sbase + wg * RING_BYTES + ((t + 1) & 1) * STAGE_BYTES, fb = bars + wg * 16 + ((t + 1) & 1) * 8;
        if (elect_one()) {
          mbar_expect_tx(fb, 2 * ROW_TX);
          tma3(dst, &xmap, 0, line0, y, fb);
          tma3(dst + ROW_PITCH, &xmap, 0, line0, y + dy, fb);
        }
      };
      if (w == 0) fill(1, 0, ybase, dir);
      else if (PF1 && elect_one()) tma3_prefetch(&xmap, 0, line0, seg0 + 2 + half);
#pragma unroll 1
      for (int t = 0; t < NB; ++t) {
        mbar_wait(bars + w * 16 + ((t + 1) & 1) * 8, ((t + 1) >> 1) & 1);
        asm volatile("bar.sync %0, 288;" ::"r"(2 - w) : "memory");
        if (t + w == 0) fill(0, 1, seg0 + 2, 1);
        else if (DLY0) __nanosleep(DLY0);
        const int tn = t + 1 + w;
        if (tn < NB) fill(o, tn, ybase + dir * 2 * tn, dir);
        if (PFD > 0 && tn >= PFS && tn + PFD < NB && elect_one()) tma3_prefetch(&xmap, 0, line0, ybase + dir * (2 * (tn + PFD) + half));
      }
    }
  } else {
    asm volatile("setmaxnreg.inc.sync.aligned.u32 240;");
    const int wg = warp >> 2, w = warp & 3;
    const uint32_t fb = bars + wg * 16;
    const int g = lane >> 2, t4 = lane & 3;

    uint32_t la[12];
#pragma unroll
    for (int q = 0; q < 3; ++q)
      asm volatile("ld.shared.v4.b32 {%0,%1,%2,%3}, [%4];" : "=r"(la[4 * q]), "=r"(la[4 * q + 1]), "=r"(la[4 * q + 2]), "=r"(la[4 * q + 3])
                   : "r"(bars + 128 + q * 2048 + (tid & 127) * 16) : "memory");
    uint32_t soff = wg * RING_BYTES;
    float b2[12];
    {
      const uint32_t r[6] = {bias_v.x, bias_v.y, bias_v.z, bias_v.w, bias_u.x, bias_u.y};
#pragma unroll
      for (int j = 0; j < 6; ++j) { b2[2 * j] = 2.f * bf_lo(r[j]); b2[2 * j + 1] = 2.f * bf_hi(r[j]); }
    }
    constexpr int OROW = IMG_W * CH * 2;
    const int orow = wg ? -OROW : OROW;
    uint64_t op16 = (uint64_t)__cvta_generic_to_global(out) + (ptrdiff_t)(seg0 + wg * (4 * NB - 1)) * OROW - (ptrdiff_t)orow
                    + ((pair & 7) * 64 + 16 * w + 2 * g) * (CH * 2) + off64 + 16 * t4;
    uint64_t op8 = op16 + (int64_t)(off32 - off64 - 8 * t4);
    const uint64_t dswap = wg ? (uint64_t)((2 * W_SLOT) >> 4) : 0;
    const uint32_t bar_tx0 = 1 + wg, bar_rx0 = 2 - wg;

    constexpr int NAB = LDA + 2;
    float Z0[24], Z1[24], Z2[24], Z3[24];
    uint32_t A[NAB][4], B[NAB][4], S[3][4], D[3][4], MP[3][4], MQ[3][4];
    auto store = [&](const uint32_t (&y)[12], int n, int on, uint64_t p16, uint64_t p8) {
      if (n == 0) st128<0>(p16, on, y[0], y[1], y[2], y[3]);
      if (n == 1) st128<192>(p16, on, y[6], y[7], y[8], y[9]);
      if (n == 2) st64<0>(p8, on, y[4], y[5]);
      if (n == 3) st64<192>(p8, on, y[10], y[11]);
    };
    auto ld_addr = [&](int cg) { return la[cg] + soff; };
    auto load = [&](int cg) { ldsm4(A[cg % NAB], ld_addr(cg)); ldsm4(B[cg % NAB], ld_addr(cg) + ROW_PITCH); };
    uint32_t clk = 0;
    auto prep = [&](int r) {
#pragma unroll
      for (int i = 0; i < 4; ++i) {
        if (r < 12) S[r % 3][i] = hadd2(A[r % NAB][i], B[r % NAB][i]);
        if (r > 0) {
          const int src = ((r - 1) & ~1) + (i >> 1);
          MP[r % 3][i] = or32((r & 1) ? A[src % NAB][1 + (i & 1)] : S[src % 3][1 + (i & 1)], zero2);
        }
        if (r < 12) D[r % 3][i] = hsub2(A[r % NAB][i], B[r % NAB][i]);
        if (r > 0) {
          const int src = ((r - 1) & ~1) + (i >> 1);
          if (FA == 3 && i == 3 && r >= 2) asm volatile("lop3.b32 %0, %1, %2, %3, 0xF8;" : "=r"(MQ[r % 3][i]) : "r"((r & 1) ? B[src % NAB][1 + (i & 1)] : D[src % 3][1 + (i & 1)]), "r"(clk), "r"(zero2));
          else MQ[r % 3][i] = or32((r & 1) ? B[src % NAB][1 + (i & 1)] : D[src % 3][1 + (i & 1)], zero2);
        }
      }
    };
    mbar_wait(fb, 0);
    {
      uint32_t F[12][4], M[6][4];
      const uint64_t d3 = WDESC + dswap + zero2;
      if (LEADORD && wg == 1) asm volatile("bar.sync 3, 256;" ::: "memory");
#pragma unroll
      for (int cg = 0; cg < 12; ++cg) ldsm4(F[cg], la[cg] + (wg ? 0 : ROW_PITCH));
      if (LEADORD) {
        if (wg == 0) asm volatile("bar.arrive 3, 256;" ::: "memory");
        else asm volatile("bar.arrive 2, 288;" ::: "memory");
      }
#pragma unroll
      for (int c = 0; c < 6; ++c) {
        if (c % LG == 0) {
#pragma unroll
          for (int q = c; q < c + LG; ++q) {
            M[q][0] = or32(F[2 * q][1], zero2); M[q][1] = or32(F[2 * q][2], zero2); M[q][2] = or32(F[2 * q + 1][1], zero2); M[q][3] = or32(F[2 * q + 1][2], zero2);
          }
          wg_fence();
        }
        if (c == 0) mma48<0>(Z3, F[0], d3, d_outer(0, 3));
        else mma48<1>(Z3, F[2 * c], d3, d_outer(2 * c, 3));
        mma48<1>(Z3, F[2 * c + 1], d3, d_outer(2 * c + 1, 3));
        mma48<1>(Z3, M[c], d3, d_mid(c, 3));
      }
      wg_commit();
    }
    if (!LEADORD && wg == 1) asm volatile("bar.arrive 2, 288;" ::: "memory");
    wg_wait<0>();
    pin(Z3);
#pragma unroll
    for (int i = 0; i < 24; ++i) {
      Z0[i] = 0.f;
      Z1[i] = Z3[i] + b2[(i >> 2) * 2 + (i & 1)];
      Z2[i] = -Z3[i];
    }
#pragma unroll
    for (int i = 0; i < PAD; ++i) asm volatile("pmevent 0;" ::: "memory");
    for (int t = 0; t < NB; ++t) {
      uint32_t yo[12], ye[12];
      float ev[2];
#pragma unroll
      for (int i = 0; i < 12; ++i) { asm volatile("" : "=r"(yo[i])); asm volatile("" : "=r"(ye[i])); }
      asm volatile("" : "=f"(ev[0])); asm volatile("" : "=f"(ev[1]));
      const uint64_t oq16 = op16 + orow, oq8 = op8 + orow;
      auto block = [&](int k) {
        if (t > (int)((k & 1) ? zero : zero2)) {
#pragma unroll
          for (int nn = 0; nn < 24 / NCH; ++nn) {
            const int n = k * (24 / NCH) + nn;
            const int e = n / 12, j = (n % 12) >> 1, u = n & 1, i = 4 * j + 2 * e + u;
            if (u == 0) yo[6 * e + j] = pack_bf16(Z0[i], Z0[i + 1]);
            const float sm = Z1[i] + Z2[i], df = Z1[i] - Z2[i];
            const float p = fmaf(0.5f, sm, -Z0[i]);
            ev[u] = fmaf(0.5f, df, -Z3[i]);
            Z0[i] = p;
            Z1[i] = (p + b2[2 * j + u]) + Z3[i];
            Z2[i] = p - Z3[i];
            if (u == 1) ye[6 * e + j] = pack_bf16(ev[0], ev[1]);
            if (n % 12 == 6) store(yo, e, t - 1, op16, op8);
            if (n % 12 == 8) store(ye, e, 1, oq16, oq8);
            if (n % 12 == 10) store(yo, 2 + e, t - 1, op16, op8);
            if (n % 12 == 11) store(ye, 2 + e, 1, oq16, oq8);
            if (n == 23) { op16 = oq16 + orow; op8 = oq8 + orow; }
          }
        }
      };
      if (!SKIP0 || t > 0) {
#pragma unroll
        for (int k = 0; k < NCH - PRE0; ++k) block(k);
      }
#pragma unroll
      for (int k = NCH - PRE0; k <= NCH; ++k) {
        if (k == NCH - PRE0) {
          soff = wg * RING_BYTES + ((t + 1) & 1) * STAGE_BYTES;
          asm volatile("bar.sync %0, 288;" ::"r"(bar_rx0) : "memory");
          load(0);
        }
        if (k == NCH - PRE1) load(1);
        if (LDA > 2 && k == NCH - PRE2) load(2);
        if (k < NCH) block(k);
      }
      prep(0);
      const uint64_t dbase = WDESC + (uint64_t)(t & zero), db0 = dbase - dswap, db3 = dbase + dswap;
#pragma unroll
      for (int r = 0; r < 13; ++r) {
        if (r == 0) wg_fence();
        if (r < 12) {
          mma48<1>(Z0, A[r % NAB], db0, d_outer(r, 0));
          mma48<1>(Z1, S[r % 3], dbase, d_outer(r, 1));
          if (SPLIT == 2) wg_commit();
          mma48<1>(Z2, D[r % 3], dbase, d_outer(r, 2));
          if (SPLIT == 3) wg_commit();
          if (r == 0) mma48<0>(Z3, B[r % NAB], db3, d_outer(r, 3));
          else mma48<1>(Z3, B[r % NAB], db3, d_outer(r, 3));
        }
        if (SPLIT == 4 && r > 0 && r < 12) wg_commit();
        if (r > 0) {
          const int c = (r - 1) >> 1;
          if (r & 1) { mma48<1>(Z0, MP[r % 3], db0, d_mid(c, 0)); mma48<1>(Z3, MQ[r % 3], db3, d_mid(c, 3)); }
          else       { mma48<1>(Z1, MP[r % 3], dbase, d_mid(c, 1)); mma48<1>(Z2, MQ[r % 3], dbase, d_mid(c, 2)); }
        }
        wg_commit();
        if (r + LDA < 12) load(r + LDA);
        static_assert(PACE_S0 + LDA >= 11, "the gate arrival doubles as the stage release");
        if (r == PACE_S0 && t + wg < NB) asm volatile("bar.arrive %0, 288;" ::"r"(bar_tx0) : "memory");
        if (r < 12) prep(r + 1);
        if (r < 12) { if (r < NBRK) sched_break(zero); if (FA != 2) wg_fence(); wg_wait<(SPLIT ? 3 : 1)>(); if (FA == 1 || FA == 2) asm volatile("pmevent 0;" ::: "memory"); if (FA == 3 && r < 11) asm volatile("mov.u32 %0, %clock;" : "=r"(clk) :: "memory"); if (FA == 2) wg_fence(); } else wg_wait<0>();
      }
      pin(Z0); pin(Z1); pin(Z2); pin(Z3);
    }
    {
      const uint32_t xch = sbase + STAGE_BYTES + (tid & 127) * 16;
      uint32_t yo[12], ye[12], y2[12], y3[12];
#pragma unroll
      for (int k = 0; k < 12; ++k) yo[k] = pack_bf16(Z0[4 * (k % 6) + 2 * (k / 6)], Z0[4 * (k % 6) + 2 * (k / 6) + 1]);
#pragma unroll
      for (int n = 0; n < 4; ++n) store(yo, n, 1, op16, op8);
#pragma unroll
      for (int j = 0; j < 6; ++j) {
        if (TFENCE) asm volatile("pmevent 0;" ::: "memory");
        float ev[4];
#pragma unroll
        for (int u = 0; u < 4; ++u) {
          const int i = 4 * j + u;
          ev[u] = fmah(fsub(Z1[i], Z2[i]), Z3[i]);
          Z0[i] = fmah(fadd(Z1[i], Z2[i]), Z0[i]);
        }
        ye[j] = pack_bf16(ev[0], ev[1]); ye[6 + j] = pack_bf16(ev[2], ev[3]);
        asm volatile("{\n.reg .pred p;\nsetp.le.s32 p, %5, 0;\n@p st.shared.v4.f32 [%4], {%0,%1,%2,%3};\n}\n"
                     ::"f"(Z0[4 * j]), "f"(Z0[4 * j + 1]), "f"(Z0[4 * j + 2]), "f"(Z0[4 * j + 3]), "r"(xch + j * 4096), "r"(wg + zero) : "memory");
        asm volatile("{\n.reg .pred p;\nsetp.le.s32 p, %5, 0;\n@p st.shared.v4.f32 [%4], {%0,%1,%2,%3};\n}\n"
                     ::"f"(Z3[4 * j]), "f"(Z3[4 * j + 1]), "f"(Z3[4 * j + 2]), "f"(Z3[4 * j + 3]), "r"(xch + j * 4096 + 2048), "r"(wg + zero2) : "memory");
        if (j == 3) { store(ye, 0, 1, op16 + orow, op8 + orow); store(ye, 1, 1, op16 + orow, op8 + orow); }
        if (j == 5) { store(ye, 2, 1, op16 + orow, op8 + orow); store(ye, 3, 1, op16 + orow, op8 + orow); }
      }
      if (wg == 0) asm volatile("bar.arrive 3, 256;" ::: "memory");
      else asm volatile("bar.sync 3, 256;" ::: "memory");
#pragma unroll
      for (int j = 0; j < 6; ++j) {
        asm volatile("{\n.reg .pred p;\nsetp.gt.s32 p, %5, 0;\n@p ld.shared.v4.f32 {%0,%1,%2,%3}, [%4];\n}\n"
                     : "+f"(Z1[4 * j]), "+f"(Z1[4 * j + 1]), "+f"(Z1[4 * j + 2]), "+f"(Z1[4 * j + 3]) : "r"(xch + j * 4096), "r"(wg + zero) : "memory");
        asm volatile("{\n.reg .pred p;\nsetp.gt.s32 p, %5, 0;\n@p ld.shared.v4.f32 {%0,%1,%2,%3}, [%4];\n}\n"
                     : "+f"(Z2[4 * j]), "+f"(Z2[4 * j + 1]), "+f"(Z2[4 * j + 2]), "+f"(Z2[4 * j + 3]) : "r"(xch + j * 4096 + 2048), "r"(wg + zero2) : "memory");
      }
#pragma unroll
      for (int j = 0; j < 6; ++j) {
        if (TFENCE && (j == 2 || j == 4)) asm volatile("pmevent 0;" ::: "memory");
#pragma unroll
        for (int e = 0; e < 2; ++e) {
          const int i = 4 * j + 2 * e;
          y2[6 * e + j] = pack_bf16(fadd(Z0[i], Z2[i]), fadd(Z0[i + 1], Z2[i + 1]));
          y3[6 * e + j] = pack_bf16(fadd(Z3[i], Z1[i]), fadd(Z3[i + 1], Z1[i + 1]));
        }
        if (j == 3 || j == 5) {
#pragma unroll
          for (int n = j - 3; n < j - 1; ++n) {
            store(y2, n, wg + zero, op16 + 2 * orow, op8 + 2 * orow);
            store(y3, n, wg + zero2, op16 + 3 * orow, op8 + 3 * orow);
          }
        }
      }
    }
  }
}

typedef CUresult (*EncodeTiledFn)(CUtensorMap*, CUtensorMapDataType, cuuint32_t, void*, const cuuint64_t*,
                                  const cuuint64_t*, const cuuint32_t*, const cuuint32_t*, CUtensorMapInterleave,
                                  CUtensorMapSwizzle, CUtensorMapL2promotion, CUtensorMapFloatOOBfill);

}

extern "C" void kernel_launch(void* const* d_in, const int* in_sizes, int n_in, void* d_out, int out_size) {
  (void)in_sizes; (void)n_in; (void)out_size;
  static EncodeTiledFn encode = nullptr;
  if (!encode) {
    void* fn = nullptr;
    cudaDriverEntryPointQueryResult qr;
    cudaGetDriverEntryPoint("cuTensorMapEncodeTiled", &fn, cudaEnableDefault, &qr);
    encode = (EncodeTiledFn)fn;
    cudaFuncSetAttribute(conv3x3_kernel, cudaFuncAttributeMaxDynamicSharedMemorySize, SMEM_BYTES);
  }
  const cuuint32_t estr[3] = {1, 1, 1};
  CUtensorMap xmap;
  {
    const cuuint64_t dims[3] = {64, (cuuint64_t)(IMG_W * CH * 2 / 128), (cuuint64_t)IMG_H};
    const cuuint64_t strides[2] = {128, (cuuint64_t)IMG_W * CH * 2};
    const cuuint32_t box[3] = {64, ROW_LINES, 1};
    encode(&xmap, CU_TENSOR_MAP_DATA_TYPE_BFLOAT16, 3, d_in[0], dims, strides, box, estr, CU_TENSOR_MAP_INTERLEAVE_NONE,
           CU_TENSOR_MAP_SWIZZLE_128B, CU_TENSOR_MAP_L2_PROMOTION_L2_256B, CU_TENSOR_MAP_FLOAT_OOB_FILL_NONE);
  }
  conv3x3_kernel<<<128, NUM_THREADS, SMEM_BYTES, cudaStreamPerThread>>>(
      xmap, (const uint8_t*)d_in[1], (const __nv_bfloat16*)d_in[2], (__nv_bfloat16*)d_out, 0u, 0u);
}
```

```cpp
#include <cuda_runtime.h>
#include <cuda_bf16.h>
#include <cuda.h>
#include <stdint.h>

#define DEVI __device__ __forceinline__

namespace {

constexpr int IMG_H = 512, IMG_W = 512, CH = 96;
constexpr int OROW = IMG_W * CH * 2;
constexpr int NB = 16;
constexpr int ROW_LINES = 100;
constexpr int ROW_TX = ROW_LINES * 128;
constexpr int ROW_PITCH = 13312;
constexpr int STAGE_BYTES = 2 * ROW_PITCH;
constexpr int RING_BYTES = 2 * STAGE_BYTES;
constexpr int W_TAP = CH * CH * 2;
constexpr int W_RAW = 3 * W_TAP;
constexpr int W_OFF = RING_BYTES + W_RAW;
constexpr int W_SLOT = CH * 48 * 2;
constexpr int W_KW = 4 * W_SLOT;
constexpr int BAR_OFF = W_OFF + 3 * W_KW;
constexpr int LA_OFF = BAR_OFF + 128;
constexpr int SMEM_BYTES = LA_OFF + 6144;
constexpr uint32_t SMEM_BASE = 1024;
constexpr int NUM_THREADS = 384;
constexpr int LDA = 3;
constexpr int GATE_R = 8;
constexpr int PF_START = 3, PF_DIST = 2;

constexpr uint64_t WDESC = (uint64_t)((SMEM_BASE + W_OFF) >> 4) | ((uint64_t)(128 >> 4) << 32);
__host__ __device__ constexpr int w_slot(int pos) { return pos == 0 ? 2 : pos == 1 ? 1 : pos == 2 ? 3 : 0; }
__host__ __device__ constexpr uint32_t d_outer(int cg, int pos) { return (uint32_t)(((w_slot(pos) * W_SLOT + cg * 768) >> 4) | (((2 * W_KW) >> 4) << 16)); }
__host__ __device__ constexpr uint32_t d_mid(int c, int pos) { return (uint32_t)(((W_KW + w_slot(pos) * W_SLOT + c * 1536) >> 4) | ((768 >> 4) << 16)); }

DEVI uint32_t smem_u32(const void* p) { return (uint32_t)__cvta_generic_to_shared(p); }
DEVI void wg_fence() { asm volatile("wgmma.fence.sync.aligned;" ::: "memory"); }
DEVI void wg_commit() { asm volatile("wgmma.commit_group.sync.aligned;" ::: "memory"); }
template <int N> DEVI void wg_wait() { asm volatile("wgmma.wait_group.sync.aligned %0;" ::"n"(N) : "memory"); }
DEVI void proxy_fence() { asm volatile("fence.proxy.async.shared::cta;" ::: "memory"); }
DEVI void sched_fence() { asm volatile("pmevent 0;" ::: "memory"); }

DEVI void ldsm4(uint32_t (&r)[4], uint32_t addr) {
  asm volatile("ldmatrix.sync.aligned.m8n8.x4.shared.b16 {%0,%1,%2,%3}, [%4];"
               : "=r"(r[0]), "=r"(r[1]), "=r"(r[2]), "=r"(r[3]) : "r"(addr) : "memory");
}
DEVI void stsm4(uint32_t addr, uint32_t r0, uint32_t r1, uint32_t r2, uint32_t r3) {
  asm volatile("stmatrix.sync.aligned.m8n8.x4.shared.b16 [%0], {%1,%2,%3,%4};"
               ::"r"(addr), "r"(r0), "r"(r1), "r"(r2), "r"(r3) : "memory");
}
DEVI uint32_t hadd2(uint32_t a, uint32_t b) { uint32_t r; asm volatile("add.rn.bf16x2 %0, %1, %2;" : "=r"(r) : "r"(a), "r"(b)); return r; }
DEVI uint32_t hsub2(uint32_t a, uint32_t b) { uint32_t r; asm volatile("sub.rn.bf16x2 %0, %1, %2;" : "=r"(r) : "r"(a), "r"(b)); return r; }
DEVI uint32_t copy32(uint32_t a, uint32_t z) { uint32_t r; asm volatile("or.b32 %0, %1, %2;" : "=r"(r) : "r"(a), "r"(z)); return r; }
DEVI uint32_t pack_bf16(float lo, float hi) { uint32_t r; asm("cvt.rn.bf16x2.f32 %0, %1, %2;" : "=r"(r) : "f"(hi), "f"(lo)); return r; }
DEVI float fadd(float a, float b) { float r; asm volatile("add.rn.f32 %0, %1, %2;" : "=f"(r) : "f"(a), "f"(b)); return r; }
DEVI float fsub(float a, float b) { float r; asm volatile("sub.rn.f32 %0, %1, %2;" : "=f"(r) : "f"(a), "f"(b)); return r; }
DEVI float fmah(float a, float b) { float r; asm volatile("fma.rn.f32 %0, %1, 0f3F000000, %2;" : "=f"(r) : "f"(a), "f"(-b)); return r; }
DEVI float bf_lo(uint32_t v) { return __uint_as_float(v << 16); }
DEVI float bf_hi(uint32_t v) { return __uint_as_float(v & 0xffff0000u); }

DEVI void mbar_init(uint32_t bar, uint32_t cnt) { asm volatile("mbarrier.init.shared::cta.b64 [%0], %1;" ::"r"(bar), "r"(cnt) : "memory"); }
DEVI void mbar_expect_tx(uint32_t bar, uint32_t tx) { asm volatile("mbarrier.arrive.expect_tx.shared::cta.b64 _, [%0], %1;" ::"r"(bar), "r"(tx) : "memory"); }
DEVI void mbar_wait(uint32_t bar, uint32_t parity) {
  asm volatile(
      "{\n.reg .pred p;\n.reg .u32 c;\n"
      "mbarrier.try_wait.parity.shared::cta.b64 p, [%0], %1;\n"
      "@p bra.uni DONE;\n"
      "mov.u32 c, 0;\n"
      "SPIN:\n"
      "mbarrier.try_wait.parity.shared::cta.b64 p, [%0], %1, 100000;\n"
      "@p bra.uni DONE;\n"
      "add.u32 c, c, 1;\n"
      "setp.lt.u32 p, c, 0x4000;\n"
      "@p bra.uni SPIN;\n"
      "DONE:\n}\n" ::"r"(bar), "r"(parity) : "memory");
}
DEVI bool elect_one() {
  uint32_t p;
  asm volatile("{\n.reg .pred p;\nelect.sync _|p, 0xffffffff;\nselp.b32 %0, 1, 0, p;\n}\n" : "=r"(p));
  return p != 0;
}
DEVI void tma_row(uint32_t dst, const CUtensorMap* map, int line, int y, uint32_t bar) {
  asm volatile("cp.async.bulk.tensor.3d.shared::cluster.global.mbarrier::complete_tx::bytes [%0], [%1, {%3, %4, %5}], [%2];"
               ::"r"(dst), "l"(map), "r"(bar), "r"(0), "r"(line), "r"(y) : "memory");
}
DEVI void tma_row_both(uint32_t dst, const CUtensorMap* map, int line, int y, uint32_t bar) {
  asm volatile("cp.async.bulk.tensor.3d.shared::cluster.global.mbarrier::complete_tx::bytes.multicast::cluster [%0], [%1, {%3, %4, %5}], [%2], %6;"
               ::"r"(dst), "l"(map), "r"(bar), "r"(0), "r"(line), "r"(y), "h"((uint16_t)3) : "memory");
}
DEVI void tma_row_prefetch(const CUtensorMap* map, int line, int y) {
  asm volatile("cp.async.bulk.prefetch.tensor.3d.L2.global [%0, {%1, %2, %3}];" ::"l"(map), "r"(0), "r"(line), "r"(y) : "memory");
}
DEVI void bulk_load(uint32_t dst, const void* src, uint32_t bytes, uint32_t bar) {
  asm volatile("cp.async.bulk.shared::cluster.global.mbarrier::complete_tx::bytes [%0], [%1], %2, [%3];"
               ::"r"(dst), "l"(src), "r"(bytes), "r"(bar) : "memory");
}

template <int ACC>
DEVI void mma48(float (&d)[24], const uint32_t (&a)[4], uint64_t dbase, uint32_t doff) {
  const uint64_t desc = dbase + (uint64_t)doff;
  asm volatile(
      "wgmma.mma_async.sync.aligned.m64n48k16.f32.bf16.bf16 "
      "{%0,%1,%2,%3,%4,%5,%6,%7,%8,%9,%10,%11,%12,%13,%14,%15,%16,%17,%18,%19,%20,%21,%22,%23}, "
      "{%24,%25,%26,%27}, %28, %29, 1, 1, 1;\n"
      : "+f"(d[0]), "+f"(d[1]), "+f"(d[2]), "+f"(d[3]), "+f"(d[4]), "+f"(d[5]), "+f"(d[6]), "+f"(d[7]),
        "+f"(d[8]), "+f"(d[9]), "+f"(d[10]), "+f"(d[11]), "+f"(d[12]), "+f"(d[13]), "+f"(d[14]), "+f"(d[15]),
        "+f"(d[16]), "+f"(d[17]), "+f"(d[18]), "+f"(d[19]), "+f"(d[20]), "+f"(d[21]), "+f"(d[22]), "+f"(d[23])
      : "r"(a[0]), "r"(a[1]), "r"(a[2]), "r"(a[3]), "l"(desc), "n"(ACC));
}
DEVI void pin(float (&d)[24]) {
#pragma unroll
  for (int i = 0; i < 24; ++i) asm volatile("" : "+f"(d[i]) :: "memory");
}

template <int OFF>
DEVI void st128(uint64_t p, int on, uint32_t a, uint32_t b, uint32_t c, uint32_t d) {
  asm volatile("{\n.reg .pred p;\nsetp.gt.s32 p, %5, 0;\n@p st.global.v4.b32 [%0+%6], {%1,%2,%3,%4};\n}\n"
               ::"l"(p), "r"(a), "r"(b), "r"(c), "r"(d), "r"(on), "n"(OFF) : "memory");
}
template <int OFF>
DEVI void st64(uint64_t p, int on, uint32_t a, uint32_t b) {
  asm volatile("{\n.reg .pred p;\nsetp.gt.s32 p, %3, 0;\n@p st.global.v2.b32 [%0+%4], {%1,%2};\n}\n"
               ::"l"(p), "r"(a), "r"(b), "r"(on), "n"(OFF) : "memory");
}

__global__ void __cluster_dims__(2, 1, 1) __launch_bounds__(NUM_THREADS, 1)
conv3x3_kernel(const __grid_constant__ CUtensorMap xmap, const uint8_t* __restrict__ wgt,
               const __nv_bfloat16* __restrict__ bias, __nv_bfloat16* __restrict__ out, uint32_t zero, uint32_t zero2) {
  extern __shared__ __align__(1024) uint8_t smem_raw[];
  if (threadIdx.x < 11) asm volatile("prefetch.global.L2 [%0];" ::"l"(wgt + min((blockIdx.x * 11 + threadIdx.x) * 128, 3 * W_RAW - 128)));
  const uint32_t sbase = smem_u32(smem_raw);
  const uint32_t bars = sbase + BAR_OFF;
  const int tid = threadIdx.x, warp = __shfl_sync(0xffffffffu, tid >> 5, 0), lane = tid & 31;
  const int half = blockIdx.x & 1, pair = blockIdx.x >> 1;
  const int off64 = half * 128, off32 = 64 + half * 32;
  const int line0 = (pair & 7) * 96 - 2, seg0 = (pair >> 3) * (4 * NB);

  if (warp == 11) {
    if (elect_one()) {
#pragma unroll
      for (int kw = 0; kw < 3; ++kw) mbar_init(bars + 64 + 8 * kw, 1);
      proxy_fence();
#pragma unroll
      for (int kw = 0; kw < 3; ++kw) {
        mbar_expect_tx(bars + 64 + 8 * kw, W_RAW);
#pragma unroll
        for (int kh = 0; kh < 3; ++kh)
          bulk_load(sbase + RING_BYTES + ((kw + 1) % 3) * W_RAW + kh * W_TAP, wgt + (kh * 3 + kw) * W_TAP, W_TAP, bars + 64 + 8 * kw);
      }
      sched_fence();
#pragma unroll
      for (int i = 0; i < 8; ++i) mbar_init(bars + 8 * i, 1);
      asm volatile("fence.mbarrier_init.release.cluster;" ::: "memory");
      proxy_fence();
      mbar_expect_tx(bars, ROW_TX);
      tma_row(sbase + ROW_PITCH, &xmap, line0, seg0 - 1, bars);
      mbar_expect_tx(bars + 16, ROW_TX);
      tma_row(sbase, &xmap, line0, seg0 + 4 * NB, bars + 16);
      mbar_expect_tx(bars + 8, 2 * ROW_TX);
      tma_row(sbase + STAGE_BYTES, &xmap, line0, seg0, bars + 8);
      tma_row(sbase + STAGE_BYTES + ROW_PITCH, &xmap, line0, seg0 + 1, bars + 8);
    }
  }
  if ((sbase & 0xFFFFFFu) != SMEM_BASE) __trap();
  const uint4 bias_v = __ldg(reinterpret_cast<const uint4*>(bias + off64 / 2 + 8 * (lane & 3)));
  const uint2 bias_u = __ldg(reinterpret_cast<const uint2*>(bias + off32 / 2 + 4 * (lane & 3)));
  __syncthreads();
  asm volatile("barrier.cluster.arrive.relaxed.aligned;" ::: "memory");
  {
    const int p = 16 * (warp & 3) + 2 * (lane & 7) - 1 + (lane >> 3);
    const uint32_t off = 192 * p + 256 + 64 * (warp >> 2), a0 = sbase + (off ^ (((off >> 7) & 7) << 4));
    asm volatile("st.shared.v4.b32 [%0], {%1,%2,%3,%4};" ::"r"(sbase + LA_OFF + tid * 16), "r"(a0), "r"(a0 ^ 16), "r"(a0 ^ 32), "r"(a0 ^ 48) : "memory");
  }
  {
    const int g = lane >> 2, t4 = lane & 3;
    uint32_t blk = sbase + W_OFF + warp * 768;
#pragma unroll 1
    for (int kw = 0; kw < 3; ++kw, blk += W_KW) {
      const uint32_t src = sbase + RING_BYTES + (kw == 2 ? 0 : kw + 1) * W_RAW + (warp * 8 + g) * 192;
      mbar_wait(bars + 64 + 8 * kw, 0);
      uint32_t raw[3][6];
#pragma unroll
      for (int kh = 0; kh < 3; ++kh) {
        asm volatile("ld.shared.v4.b32 {%0,%1,%2,%3}, [%4];" : "=r"(raw[kh][0]), "=r"(raw[kh][1]), "=r"(raw[kh][2]), "=r"(raw[kh][3])
                     : "r"(src + kh * W_TAP + off64 + 16 * t4) : "memory");
        asm volatile("ld.shared.v2.b32 {%0,%1}, [%2];" : "=r"(raw[kh][4]), "=r"(raw[kh][5])
                     : "r"(src + kh * W_TAP + off32 + 8 * t4) : "memory");
      }
      if (kw < 2) __syncthreads();
      const uint32_t d4 = blk + lane * 16;
      const uint32_t d2 = blk + 512 + (lane & 15) * 16 + (lane >> 4) * (2 * W_SLOT);
      stsm4(d4, raw[0][0], raw[0][1], raw[0][2], raw[0][3]);
      stsm4(d4 + 2 * W_SLOT, raw[2][0], raw[2][1], raw[2][2], raw[2][3]);
      stsm4(d2, raw[0][4], raw[0][5], raw[2][4], raw[2][5]);
      uint32_t u1[6], u2[6];
#pragma unroll
      for (int j = 0; j < 6; ++j) {
        const float tl = bf_lo(raw[0][j]) + bf_lo(raw[2][j]), th = bf_hi(raw[0][j]) + bf_hi(raw[2][j]);
        const float ml = bf_lo(raw[1][j]), mh = bf_hi(raw[1][j]);
        u1[j] = pack_bf16(tl + ml, th + mh);
        u2[j] = pack_bf16(tl - ml, th - mh);
      }
      stsm4(d4 + W_SLOT, u1[0], u1[1], u1[2], u1[3]);
      stsm4(d4 + 3 * W_SLOT, u2[0], u2[1], u2[2], u2[3]);
      stsm4(d2 + W_SLOT, u1[4], u1[5], u2[4], u2[5]);
    }
    proxy_fence();
  }
  asm volatile("barrier.cluster.wait.aligned;" ::: "memory");
  __syncthreads();

  if (warp >= 8) {
    asm volatile("setmaxnreg.dec.sync.aligned.u32 24;");
    if (warp < 10) {
      const int w = warp - 8, o = w ^ 1, dir = 1 - 2 * o;
      const int ybase = seg0 + o * (4 * NB - 1);
      uint32_t peer_free;
      asm volatile("mapa.shared::cluster.u32 %0, %1, %2;" : "=r"(peer_free) : "r"(bars + 32 + 16 * w), "r"(half ^ 1));
      auto fill = [&](int wg, int t, int y, int dy) {
        const uint32_t dst = sbase + wg * RING_BYTES + ((t + 1) & 1) * STAGE_BYTES, fb = bars + wg * 16 + ((t + 1) & 1) * 8;
        if (elect_one()) {
          mbar_expect_tx(fb, 2 * ROW_TX);
          tma_row(dst, &xmap, line0, y, fb);
          tma_row(dst + ROW_PITCH, &xmap, line0, y + dy, fb);
        }
      };
      if (w == 0) fill(1, 0, ybase, dir);
      else if (elect_one()) tma_row_prefetch(&xmap, line0, seg0 + 2 + half);
#pragma unroll 1
      for (int t = 0; t < NB; ++t) {
        mbar_wait(bars + w * 16 + ((t + 1) & 1) * 8, ((t + 1) >> 1) & 1);
        asm volatile("bar.sync %0, 288;" ::"r"(2 - w) : "memory");
        if (t + w == 0) fill(0, 1, seg0 + 2, 1);
        const int tn = t + 1 + w;
        if (tn < NB) {
          const uint32_t dst = sbase + o * RING_BYTES + ((tn + 1) & 1) * STAGE_BYTES, fb = bars + o * 16 + ((tn + 1) & 1) * 8;
          if (elect_one()) {
            mbar_expect_tx(fb, 2 * ROW_TX);
            asm volatile("mbarrier.arrive.relaxed.cluster.shared::cluster.b64 _, [%0];" ::"r"(peer_free + (t & 1) * 8) : "memory");
          }
          mbar_wait(bars + 32 + 16 * w + (t & 1) * 8, (t >> 1) & 1);
          if (elect_one()) tma_row_both(dst + half * ROW_PITCH, &xmap, line0, ybase + dir * (2 * tn + half), fb);
        }
        if (tn >= PF_START && tn + PF_DIST < NB && elect_one()) tma_row_prefetch(&xmap, line0, ybase + dir * (2 * (tn + PF_DIST) + half));
      }
    }
  } else {
    asm volatile("setmaxnreg.inc.sync.aligned.u32 240;");
    const int wg = warp >> 2, w = warp & 3;
    const int g = lane >> 2, t4 = lane & 3;

    uint32_t la[12];
#pragma unroll
    for (int q = 0; q < 3; ++q)
      asm volatile("ld.shared.v4.b32 {%0,%1,%2,%3}, [%4];" : "=r"(la[4 * q]), "=r"(la[4 * q + 1]), "=r"(la[4 * q + 2]), "=r"(la[4 * q + 3])
                   : "r"(sbase + LA_OFF + q * 2048 + (tid & 127) * 16) : "memory");
    uint32_t soff = wg * RING_BYTES;
    float b2[12];
    {
      const uint32_t r[6] = {bias_v.x, bias_v.y, bias_v.z, bias_v.w, bias_u.x, bias_u.y};
#pragma unroll
      for (int j = 0; j < 6; ++j) { b2[2 * j] = 2.f * bf_lo(r[j]); b2[2 * j + 1] = 2.f * bf_hi(r[j]); }
    }
    const int orow = wg ? -OROW : OROW;
    uint64_t op16 = (uint64_t)__cvta_generic_to_global(out) + (ptrdiff_t)(seg0 + wg * (4 * NB - 1)) * OROW - (ptrdiff_t)orow
                    + ((pair & 7) * 64 + 16 * w + 2 * g) * (CH * 2) + off64 + 16 * t4;
    uint64_t op8 = op16 + (int64_t)(off32 - off64 - 8 * t4);
    op16 -= 2 * (int64_t)orow; op8 -= 2 * (int64_t)orow;
    uint64_t oq16 = op16 + orow, oq8 = op8 + orow;
    const int64_t ostep = 2 * (int64_t)orow;
    auto advance = [&](uint64_t& p) { asm volatile("add.s64 %0, %0, %1;" : "+l"(p) : "l"(ostep)); };
    const uint64_t dswap = wg ? (uint64_t)((2 * W_SLOT) >> 4) : 0;

    constexpr int NAB = LDA + 2;
    float Z0[24], Z1[24], Z2[24], Z3[24];
    uint32_t A[NAB][4], B[NAB][4], S[3][4], D[3][4], MP[3][4], MQ[3][4];
    auto store = [&](const uint32_t (&y)[12], int n, int on, uint64_t p16, uint64_t p8) {
      if (n == 0) st128<0>(p16, on, y[0], y[1], y[2], y[3]);
      if (n == 1) st128<192>(p16, on, y[6], y[7], y[8], y[9]);
      if (n == 2) st64<0>(p8, on, y[4], y[5]);
      if (n == 3) st64<192>(p8, on, y[10], y[11]);
    };
    auto load = [&](int cg) { ldsm4(A[cg % NAB], la[cg] + soff); ldsm4(B[cg % NAB], la[cg] + soff + ROW_PITCH); };
    const uint32_t vzero = __shfl_sync(0xffffffffu, (uint32_t)tid & zero2, lane);
    uint32_t clk = 0;
    auto prep = [&](int r) {
#pragma unroll
      for (int i = 0; i < 4; ++i) {
        const int src = ((r - 1) & ~1) + (i >> 1), k = 1 + (i & 1);
        if (r < 12) S[r % 3][i] = hadd2(A[r % NAB][i], B[r % NAB][i]);
        if (r > 0) MP[r % 3][i] = copy32((r & 1) ? A[src % NAB][k] : S[src % 3][k], zero2);
        if (r < 12) D[r % 3][i] = hsub2(A[r % NAB][i], B[r % NAB][i]);
        if (r > 0) {
          const uint32_t v = (r & 1) ? B[src % NAB][k] : D[src % 3][k];
          if (i == 3 && r >= 2) asm volatile("lop3.b32 %0, %1, %2, %3, 0xF8;" : "=r"(MQ[r % 3][i]) : "r"(v), "r"(clk), "r"(vzero));
          else MQ[r % 3][i] = copy32(v, zero2);
        }
      }
    };

    mbar_wait(bars + wg * 16, 0);
    {
      uint32_t F[12][4], M[6][4];
      const uint64_t d3 = WDESC + dswap + zero2;
      if (wg == 1) asm volatile("bar.sync 3, 256;" ::: "memory");
#pragma unroll
      for (int cg = 0; cg < 12; ++cg) ldsm4(F[cg], la[cg] + (wg ? 0 : ROW_PITCH));
      if (wg == 0) asm volatile("bar.arrive 3, 256;" ::: "memory");
      else asm volatile("bar.arrive 2, 288;" ::: "memory");
#pragma unroll
      for (int c = 0; c < 6; ++c) {
        M[c][0] = copy32(F[2 * c][1], zero2); M[c][1] = copy32(F[2 * c][2], zero2);
        M[c][2] = copy32(F[2 * c + 1][1], zero2); M[c][3] = copy32(F[2 * c + 1][2], zero2);
        wg_fence();
        if (c == 0) mma48<0>(Z3, F[0], d3, d_outer(0, 3));
        else mma48<1>(Z3, F[2 * c], d3, d_outer(2 * c, 3));
        mma48<1>(Z3, F[2 * c + 1], d3, d_outer(2 * c + 1, 3));
        mma48<1>(Z3, M[c], d3, d_mid(c, 3));
      }
      wg_commit();
    }
    wg_wait<0>();
    pin(Z3);
#pragma unroll
    for (int i = 0; i < 24; ++i) {
      Z0[i] = 0.f;
      Z1[i] = Z3[i] + b2[(i >> 2) * 2 + (i & 1)];
      Z2[i] = -Z3[i];
    }
#pragma unroll
    for (int i = 0; i < 4; ++i) { A[11 % NAB][i] = 0; B[11 % NAB][i] = 0; S[11 % 3][i] = 0; D[11 % 3][i] = 0; MP[12 % 3][i] = 0; MQ[12 % 3][i] = 0; }

    for (int t = 0; t < NB; ++t) {
      uint32_t yo[12], ye[12];
#pragma unroll
      for (int i = 0; i < 4; ++i) {
        yo[i] = A[11 % NAB][i]; yo[6 + i] = B[11 % NAB][i]; ye[i] = S[11 % 3][i]; ye[6 + i] = D[11 % 3][i];
        yo[4 + (i & 1) + 6 * (i >> 1)] = MP[12 % 3][i]; ye[4 + (i & 1) + 6 * (i >> 1)] = MQ[12 % 3][i];
      }
      auto block = [&](int k) {
        if (t > (int)((k & 1) ? zero : zero2)) {
          float ev[2];
#pragma unroll
          for (int u = 0; u < 2; ++u) {
            const int e = k / 6, j = k % 6, i = 4 * j + 2 * e + u;
            if (u == 0) yo[k] = pack_bf16(Z0[i], Z0[i + 1]);
            const float sm = Z1[i] + Z2[i], df = Z1[i] - Z2[i];
            const float p = fmaf(0.5f, sm, -Z0[i]);
            ev[u] = fmaf(0.5f, df, -Z3[i]);
            Z0[i] = p;
            Z1[i] = (p + b2[2 * j + u]) + Z3[i];
            Z2[i] = p - Z3[i];
            if (u == 1) ye[k] = pack_bf16(ev[0], ev[1]);
            if (j == 3 && u == 0) store(yo, e, t - 1, op16, op8);
            if (j == 4 && u == 0) store(ye, e, 1, oq16, oq8);
            if (j == 5 && u == 0) store(yo, 2 + e, t - 1, op16, op8);
            if (j == 5 && u == 1) store(ye, 2 + e, 1, oq16, oq8);
            if (k == 0 && u == 0) { advance(op16); advance(op8); }
            if (k == 1 && u == 0) { advance(oq16); advance(oq8); }
          }
        }
      };
      if (t > 0) {
#pragma unroll
        for (int k = 0; k < 10; ++k) block(k);
      }
      soff = wg * RING_BYTES + ((t + 1) & 1) * STAGE_BYTES;
      if (wg) asm volatile("bar.sync 1, 288;" ::: "memory"); else asm volatile("bar.sync 2, 288;" ::: "memory");
      load(0);
      block(10);
      load(1);
      block(11);
      load(2);
      prep(0);
      const uint64_t dbase = WDESC + (uint64_t)(t & zero), db0 = dbase - dswap, db3 = dbase + dswap;
      wg_fence();
#pragma unroll
      for (int r = 0; r < 13; ++r) {
        if (r < 12) {
          mma48<1>(Z0, A[r % NAB], db0, d_outer(r, 0));
          mma48<1>(Z1, S[r % 3], dbase, d_outer(r, 1));
          mma48<1>(Z2, D[r % 3], dbase, d_outer(r, 2));
          if (r == 0) mma48<0>(Z3, B[r % NAB], db3, d_outer(r, 3));
          else mma48<1>(Z3, B[r % NAB], db3, d_outer(r, 3));
        }
        if (r > 0) {
          const int c = (r - 1) >> 1;
          if (r & 1) { mma48<1>(Z0, MP[r % 3], db0, d_mid(c, 0)); mma48<1>(Z3, MQ[r % 3], db3, d_mid(c, 3)); }
          else       { mma48<1>(Z1, MP[r % 3], dbase, d_mid(c, 1)); mma48<1>(Z2, MQ[r % 3], dbase, d_mid(c, 2)); }
        }
        wg_commit();
        if (r + LDA < 12) load(r + LDA);
        static_assert(LDA == 3 && GATE_R + LDA >= 11, "the gate arrival doubles as the stage release");
        if (r == GATE_R && t + wg < NB) asm volatile("bar.arrive %0, 288;" ::"r"(1 + wg) : "memory");
        if (r < 12) {
          prep(r + 1);
          wg_fence();
          wg_wait<1>();
          if (r < 11) asm volatile("mov.u32 %0, %clock;" : "=r"(clk) :: "memory");
        } else {
          wg_wait<0>();
        }
      }
      pin(Z0); pin(Z1); pin(Z2); pin(Z3);
    }
    advance(op16); advance(op8);

    {
      const uint32_t xch = sbase + STAGE_BYTES + (tid & 127) * 16;
      uint32_t yo[12], ye[12], y2[12], y3[12];
#pragma unroll
      for (int k = 0; k < 12; ++k) yo[k] = pack_bf16(Z0[4 * (k % 6) + 2 * (k / 6)], Z0[4 * (k % 6) + 2 * (k / 6) + 1]);
#pragma unroll
      for (int n = 0; n < 4; ++n) store(yo, n, 1, op16, op8);
#pragma unroll
      for (int j = 0; j < 6; ++j) {
        sched_fence();
        float ev[4];
#pragma unroll
        for (int u = 0; u < 4; ++u) {
          const int i = 4 * j + u;
          ev[u] = fmah(fsub(Z1[i], Z2[i]), Z3[i]);
          Z0[i] = fmah(fadd(Z1[i], Z2[i]), Z0[i]);
        }
        ye[j] = pack_bf16(ev[0], ev[1]); ye[6 + j] = pack_bf16(ev[2], ev[3]);
        asm volatile("{\n.reg .pred p;\nsetp.le.s32 p, %5, 0;\n@p st.shared.v4.f32 [%4], {%0,%1,%2,%3};\n}\n"
                     ::"f"(Z0[4 * j]), "f"(Z0[4 * j + 1]), "f"(Z0[4 * j + 2]), "f"(Z0[4 * j + 3]), "r"(xch + j * 4096), "r"(wg + zero) : "memory");
        asm volatile("{\n.reg .pred p;\nsetp.le.s32 p, %5, 0;\n@p st.shared.v4.f32 [%4], {%0,%1,%2,%3};\n}\n"
                     ::"f"(Z3[4 * j]), "f"(Z3[4 * j + 1]), "f"(Z3[4 * j + 2]), "f"(Z3[4 * j + 3]), "r"(xch + j * 4096 + 2048), "r"(wg + zero2) : "memory");
        if (j == 3) { store(ye, 0, 1, op16 + orow, op8 + orow); store(ye, 1, 1, op16 + orow, op8 + orow); }
        if (j == 5) { store(ye, 2, 1, op16 + orow, op8 + orow); store(ye, 3, 1, op16 + orow, op8 + orow); }
      }
      if (wg == 0) asm volatile("bar.arrive 3, 256;" ::: "memory");
      else asm volatile("bar.sync 3, 256;" ::: "memory");
#pragma unroll
      for (int j = 0; j < 6; ++j) {
        asm volatile("{\n.reg .pred p;\nsetp.gt.s32 p, %5, 0;\n@p ld.shared.v4.f32 {%0,%1,%2,%3}, [%4];\n}\n"
                     : "+f"(Z1[4 * j]), "+f"(Z1[4 * j + 1]), "+f"(Z1[4 * j + 2]), "+f"(Z1[4 * j + 3]) : "r"(xch + j * 4096), "r"(wg + zero) : "memory");
        asm volatile("{\n.reg .pred p;\nsetp.gt.s32 p, %5, 0;\n@p ld.shared.v4.f32 {%0,%1,%2,%3}, [%4];\n}\n"
                     : "+f"(Z2[4 * j]), "+f"(Z2[4 * j + 1]), "+f"(Z2[4 * j + 2]), "+f"(Z2[4 * j + 3]) : "r"(xch + j * 4096 + 2048), "r"(wg + zero2) : "memory");
      }
#pragma unroll
      for (int j = 0; j < 6; ++j) {
        if (j == 2 || j == 4) sched_fence();
#pragma unroll
        for (int e = 0; e < 2; ++e) {
          const int i = 4 * j + 2 * e;
          y2[6 * e + j] = pack_bf16(fadd(Z0[i], Z2[i]), fadd(Z0[i + 1], Z2[i + 1]));
          y3[6 * e + j] = pack_bf16(fadd(Z3[i], Z1[i]), fadd(Z3[i + 1], Z1[i + 1]));
        }
        if (j == 3 || j == 5) {
#pragma unroll
          for (int n = j - 3; n < j - 1; ++n) {
            store(y2, n, wg + zero, op16 + 2 * orow, op8 + 2 * orow);
            store(y3, n, wg + zero2, op16 + 3 * orow, op8 + 3 * orow);
          }
        }
      }
    }
  }
}

typedef CUresult (*EncodeTiledFn)(CUtensorMap*, CUtensorMapDataType, cuuint32_t, void*, const cuuint64_t*,
                                  const cuuint64_t*, const cuuint32_t*, const cuuint32_t*, CUtensorMapInterleave,
                                  CUtensorMapSwizzle, CUtensorMapL2promotion, CUtensorMapFloatOOBfill);

}

extern "C" void kernel_launch(void* const* d_in, const int* in_sizes, int n_in, void* d_out, int out_size) {
  (void)in_sizes; (void)n_in; (void)out_size;
  static EncodeTiledFn encode = nullptr;
  if (!encode) {
    void* fn = nullptr;
    cudaDriverEntryPointQueryResult qr;
    cudaGetDriverEntryPoint("cuTensorMapEncodeTiled", &fn, cudaEnableDefault, &qr);
    encode = (EncodeTiledFn)fn;
    cudaFuncSetAttribute(conv3x3_kernel, cudaFuncAttributeMaxDynamicSharedMemorySize, SMEM_BYTES);
  }
  CUtensorMap xmap;
  const cuuint64_t dims[3] = {64, (cuuint64_t)(OROW / 128), (cuuint64_t)IMG_H};
  const cuuint64_t strides[2] = {128, (cuuint64_t)OROW};
  const cuuint32_t box[3] = {64, ROW_LINES, 1};
  const cuuint32_t estr[3] = {1, 1, 1};
  encode(&xmap, CU_TENSOR_MAP_DATA_TYPE_BFLOAT16, 3, d_in[0], dims, strides, box, estr, CU_TENSOR_MAP_INTERLEAVE_NONE,
         CU_TENSOR_MAP_SWIZZLE_128B, CU_TENSOR_MAP_L2_PROMOTION_L2_256B, CU_TENSOR_MAP_FLOAT_OOB_FILL_NONE);
  conv3x3_kernel<<<128, NUM_THREADS, SMEM_BYTES, cudaStreamPerThread>>>(
      xmap, (const uint8_t*)d_in[1], (const __nv_bfloat16*)d_in[2], (__nv_bfloat16*)d_out, 0u, 0u);
}
```

```cpp
#include <cuda_runtime.h>
#include <cuda_bf16.h>
#include <cuda.h>
#include <stdint.h>

#define DEVI __device__ __forceinline__

namespace {

constexpr int IMG_H = 512, IMG_W = 512, CH = 96;
constexpr int OROW = IMG_W * CH * 2;
constexpr int NB = 16;
constexpr int ROW_LINES = 100;
constexpr int ROW_TX = ROW_LINES * 128;
constexpr int ROW_PITCH = 13312;
constexpr int STAGE_BYTES = 2 * ROW_PITCH;
constexpr int RING_BYTES = 2 * STAGE_BYTES;
constexpr int W_TAP = CH * CH * 2;
constexpr int W_RAW = 3 * W_TAP;
constexpr int W_OFF = RING_BYTES + W_RAW;
constexpr int W_SLOT = CH * 48 * 2;
constexpr int W_KW = 4 * W_SLOT;
constexpr int BAR_OFF = W_OFF + 3 * W_KW;
constexpr int LA_OFF = BAR_OFF + 128;
constexpr int SMEM_BYTES = LA_OFF + 6144;
constexpr uint32_t SMEM_BASE = 1024;
constexpr int NUM_THREADS = 384;
constexpr int LDA = 3;
constexpr int GATE_R = 8;
constexpr int PF_START = 3, PF_DIST = 2;

constexpr uint64_t WDESC = (uint64_t)((SMEM_BASE + W_OFF) >> 4) | ((uint64_t)(128 >> 4) << 32);
__host__ __device__ constexpr int w_slot(int pos) { return pos == 0 ? 2 : pos == 1 ? 1 : pos == 2 ? 3 : 0; }
__host__ __device__ constexpr uint32_t d_outer(int cg, int pos) { return (uint32_t)(((w_slot(pos) * W_SLOT + cg * 768) >> 4) | (((2 * W_KW) >> 4) << 16)); }
__host__ __device__ constexpr uint32_t d_mid(int c, int pos) { return (uint32_t)(((W_KW + w_slot(pos) * W_SLOT + c * 1536) >> 4) | ((768 >> 4) << 16)); }

DEVI uint32_t smem_u32(const void* p) { return (uint32_t)__cvta_generic_to_shared(p); }
DEVI void wg_fence() { asm volatile("wgmma.fence.sync.aligned;" ::: "memory"); }
DEVI void wg_commit() { asm volatile("wgmma.commit_group.sync.aligned;" ::: "memory"); }
template <int N> DEVI void wg_wait() { asm volatile("wgmma.wait_group.sync.aligned %0;" ::"n"(N) : "memory"); }
DEVI void proxy_fence() { asm volatile("fence.proxy.async.shared::cta;" ::: "memory"); }
DEVI void sched_fence() { asm volatile("pmevent 0;" ::: "memory"); }

DEVI void ldsm4(uint32_t (&r)[4], uint32_t addr) {
  asm volatile("ldmatrix.sync.aligned.m8n8.x4.shared.b16 {%0,%1,%2,%3}, [%4];"
               : "=r"(r[0]), "=r"(r[1]), "=r"(r[2]), "=r"(r[3]) : "r"(addr) : "memory");
}
DEVI void stsm4(uint32_t addr, uint32_t r0, uint32_t r1, uint32_t r2, uint32_t r3) {
  asm volatile("stmatrix.sync.aligned.m8n8.x4.shared.b16 [%0], {%1,%2,%3,%4};"
               ::"r"(addr), "r"(r0), "r"(r1), "r"(r2), "r"(r3) : "memory");
}
DEVI uint32_t hadd2(uint32_t a, uint32_t b) { uint32_t r; asm volatile("add.rn.bf16x2 %0, %1, %2;" : "=r"(r) : "r"(a), "r"(b)); return r; }
DEVI uint32_t hsub2(uint32_t a, uint32_t b) { uint32_t r; asm volatile("sub.rn.bf16x2 %0, %1, %2;" : "=r"(r) : "r"(a), "r"(b)); return r; }
DEVI uint32_t copy32(uint32_t a, uint32_t z) { uint32_t r; asm volatile("or.b32 %0, %1, %2;" : "=r"(r) : "r"(a), "r"(z)); return r; }
DEVI uint32_t pack_bf16(float lo, float hi) { uint32_t r; asm("cvt.rn.bf16x2.f32 %0, %1, %2;" : "=r"(r) : "f"(hi), "f"(lo)); return r; }
DEVI float fadd(float a, float b) { float r; asm volatile("add.rn.f32 %0, %1, %2;" : "=f"(r) : "f"(a), "f"(b)); return r; }
DEVI float fsub(float a, float b) { float r; asm volatile("sub.rn.f32 %0, %1, %2;" : "=f"(r) : "f"(a), "f"(b)); return r; }
DEVI float fmah(float a, float b) { float r; asm volatile("fma.rn.f32 %0, %1, 0f3F000000, %2;" : "=f"(r) : "f"(a), "f"(-b)); return r; }
DEVI float bf_lo(uint32_t v) { return __uint_as_float(v << 16); }
DEVI float bf_hi(uint32_t v) { return __uint_as_float(v & 0xffff0000u); }

DEVI void mbar_init(uint32_t bar, uint32_t cnt) { asm volatile("mbarrier.init.shared::cta.b64 [%0], %1;" ::"r"(bar), "r"(cnt) : "memory"); }
DEVI void mbar_expect_tx(uint32_t bar, uint32_t tx) { asm volatile("mbarrier.arrive.expect_tx.shared::cta.b64 _, [%0], %1;" ::"r"(bar), "r"(tx) : "memory"); }
DEVI void mbar_wait(uint32_t bar, uint32_t parity) {
  asm volatile(
      "{\n.reg .pred p;\n.reg .u32 c;\n"
      "mbarrier.try_wait.parity.shared::cta.b64 p, [%0], %1;\n"
      "@p bra.uni DONE;\n"
      "mov.u32 c, 0;\n"
      "SPIN:\n"
      "mbarrier.try_wait.parity.shared::cta.b64 p, [%0], %1, 100000;\n"
      "@p bra.uni DONE;\n"
      "add.u32 c, c, 1;\n"
      "setp.lt.u32 p, c, 0x4000;\n"
      "@p bra.uni SPIN;\n"
      "DONE:\n}\n" ::"r"(bar), "r"(parity) : "memory");
}
DEVI bool elect_one() {
  uint32_t p;
  asm volatile("{\n.reg .pred p;\nelect.sync _|p, 0xffffffff;\nselp.b32 %0, 1, 0, p;\n}\n" : "=r"(p));
  return p != 0;
}
DEVI void tma_row(uint32_t dst, const CUtensorMap* map, int line, int y, uint32_t bar) {
  asm volatile("cp.async.bulk.tensor.3d.shared::cluster.global.mbarrier::complete_tx::bytes [%0], [%1, {%3, %4, %5}], [%2];"
               ::"r"(dst), "l"(map), "r"(bar), "r"(0), "r"(line), "r"(y) : "memory");
}
DEVI void tma_row_both(uint32_t dst, const CUtensorMap* map, int line, int y, uint32_t bar) {
  asm volatile("cp.async.bulk.tensor.3d.shared::cluster.global.mbarrier::complete_tx::bytes.multicast::cluster [%0], [%1, {%3, %4, %5}], [%2], %6;"
               ::"r"(dst), "l"(map), "r"(bar), "r"(0), "r"(line), "r"(y), "h"((uint16_t)3) : "memory");
}
DEVI void tma_row_prefetch(const CUtensorMap* map, int line, int y) {
  asm volatile("cp.async.bulk.prefetch.tensor.3d.L2.global [%0, {%1, %2, %3}];" ::"l"(map), "r"(0), "r"(line), "r"(y) : "memory");
}
DEVI void bulk_load(uint32_t dst, const void* src, uint32_t bytes, uint32_t bar) {
  asm volatile("cp.async.bulk.shared::cluster.global.mbarrier::complete_tx::bytes [%0], [%1], %2, [%3];"
               ::"r"(dst), "l"(src), "r"(bytes), "r"(bar) : "memory");
}

template <int ACC>
DEVI void mma48(float (&d)[24], const uint32_t (&a)[4], uint64_t dbase, uint32_t doff) {
  const uint64_t desc = dbase + (uint64_t)doff;
  asm volatile(
      "wgmma.mma_async.sync.aligned.m64n48k16.f32.bf16.bf16 "
      "{%0,%1,%2,%3,%4,%5,%6,%7,%8,%9,%10,%11,%12,%13,%14,%15,%16,%17,%18,%19,%20,%21,%22,%23}, "
      "{%24,%25,%26,%27}, %28, %29, 1, 1, 1;\n"
      : "+f"(d[0]), "+f"(d[1]), "+f"(d[2]), "+f"(d[3]), "+f"(d[4]), "+f"(d[5]), "+f"(d[6]), "+f"(d[7]),
        "+f"(d[8]), "+f"(d[9]), "+f"(d[10]), "+f"(d[11]), "+f"(d[12]), "+f"(d[13]), "+f"(d[14]), "+f"(d[15]),
        "+f"(d[16]), "+f"(d[17]), "+f"(d[18]), "+f"(d[19]), "+f"(d[20]), "+f"(d[21]), "+f"(d[22]), "+f"(d[23])
      : "r"(a[0]), "r"(a[1]), "r"(a[2]), "r"(a[3]), "l"(desc), "n"(ACC));
}
DEVI void pin(float (&d)[24]) {
#pragma unroll
  for (int i = 0; i < 24; ++i) asm volatile("" : "+f"(d[i]) :: "memory");
}

template <int OFF>
DEVI void st128(uint64_t p, int on, uint32_t a, uint32_t b, uint32_t c, uint32_t d) {
  asm volatile("{\n.reg .pred p;\nsetp.gt.s32 p, %5, 0;\n@p st.global.v4.b32 [%0+%6], {%1,%2,%3,%4};\n}\n"
               ::"l"(p), "r"(a), "r"(b), "r"(c), "r"(d), "r"(on), "n"(OFF) : "memory");
}
template <int OFF>
DEVI void st64(uint64_t p, int on, uint32_t a, uint32_t b) {
  asm volatile("{\n.reg .pred p;\nsetp.gt.s32 p, %3, 0;\n@p st.global.v2.b32 [%0+%4], {%1,%2};\n}\n"
               ::"l"(p), "r"(a), "r"(b), "r"(on), "n"(OFF) : "memory");
}

__global__ void __cluster_dims__(2, 1, 1) __launch_bounds__(NUM_THREADS, 1)
conv3x3_kernel(const __grid_constant__ CUtensorMap xmap, const uint8_t* __restrict__ wgt,
               const __nv_bfloat16* __restrict__ bias, __nv_bfloat16* __restrict__ out, uint32_t zero, uint32_t zero2) {
  extern __shared__ __align__(1024) uint8_t smem_raw[];
  if (threadIdx.x < 11) asm volatile("prefetch.global.L2 [%0];" ::"l"(wgt + min((blockIdx.x * 11 + threadIdx.x) * 128, 3 * W_RAW - 128)));
  const uint32_t sbase = smem_u32(smem_raw);
  const uint32_t bars = sbase + BAR_OFF;
  const int tid = threadIdx.x, warp = __shfl_sync(0xffffffffu, tid >> 5, 0), lane = tid & 31;
  const int half = blockIdx.x & 1, pair = blockIdx.x >> 1;
  const int off64 = half * 128, off32 = 64 + half * 32;
  const int line0 = (pair & 7) * 96 - 2, seg0 = (pair >> 3) * (4 * NB);

  if (warp == 11) {
    if (elect_one()) {
#pragma unroll
      for (int kw = 0; kw < 3; ++kw) mbar_init(bars + 64 + 8 * kw, 1);
      proxy_fence();
#pragma unroll
      for (int kw = 0; kw < 3; ++kw) {
        mbar_expect_tx(bars + 64 + 8 * kw, W_RAW);
#pragma unroll
        for (int kh = 0; kh < 3; ++kh)
          bulk_load(sbase + RING_BYTES + ((kw + 1) % 3) * W_RAW + kh * W_TAP, wgt + (kh * 3 + kw) * W_TAP, W_TAP, bars + 64 + 8 * kw);
      }
      sched_fence();
#pragma unroll
      for (int i = 0; i < 8; ++i) mbar_init(bars + 8 * i, 1);
      asm volatile("fence.mbarrier_init.release.cluster;" ::: "memory");
      proxy_fence();
      mbar_expect_tx(bars, ROW_TX);
      tma_row(sbase + ROW_PITCH, &xmap, line0, seg0 - 1, bars);
      mbar_expect_tx(bars + 16, ROW_TX);
      tma_row(sbase, &xmap, line0, seg0 + 4 * NB, bars + 16);
      mbar_expect_tx(bars + 8, 2 * ROW_TX);
      tma_row(sbase + STAGE_BYTES, &xmap, line0, seg0, bars + 8);
      tma_row(sbase + STAGE_BYTES + ROW_PITCH, &xmap, line0, seg0 + 1, bars + 8);
      tma_row_prefetch(&xmap, line0, seg0 + 4 * NB - 1 - half);
    }
  }
  if ((sbase & 0xFFFFFFu) != SMEM_BASE) __trap();
  const uint4 bias_v = __ldg(reinterpret_cast<const uint4*>(bias + off64 / 2 + 8 * (lane & 3)));
  const uint2 bias_u = __ldg(reinterpret_cast<const uint2*>(bias + off32 / 2 + 4 * (lane & 3)));
  __syncthreads();
  asm volatile("barrier.cluster.arrive.relaxed.aligned;" ::: "memory");
  {
    const int p = 16 * (warp & 3) + 2 * (lane & 7) - 1 + (lane >> 3);
    const uint32_t off = 192 * p + 256 + 64 * (warp >> 2), a0 = sbase + (off ^ (((off >> 7) & 7) << 4));
    asm volatile("st.shared.v4.b32 [%0], {%1,%2,%3,%4};" ::"r"(sbase + LA_OFF + tid * 16), "r"(a0), "r"(a0 ^ 16), "r"(a0 ^ 32), "r"(a0 ^ 48) : "memory");
  }
  {
    const int g = lane >> 2, t4 = lane & 3;
    uint32_t blk = sbase + W_OFF + warp * 768;
#pragma unroll 1
    for (int kw = 0; kw < 3; ++kw, blk += W_KW) {
      const uint32_t src = sbase + RING_BYTES + (kw == 2 ? 0 : kw + 1) * W_RAW + (warp * 8 + g) * 192;
      mbar_wait(bars + 64 + 8 * kw, 0);
      uint32_t raw[3][6];
#pragma unroll
      for (int kh = 0; kh < 3; ++kh) {
        asm volatile("ld.shared.v4.b32 {%0,%1,%2,%3}, [%4];" : "=r"(raw[kh][0]), "=r"(raw[kh][1]), "=r"(raw[kh][2]), "=r"(raw[kh][3])
                     : "r"(src + kh * W_TAP + off64 + 16 * t4) : "memory");
        asm volatile("ld.shared.v2.b32 {%0,%1}, [%2];" : "=r"(raw[kh][4]), "=r"(raw[kh][5])
                     : "r"(src + kh * W_TAP + off32 + 8 * t4) : "memory");
      }
      if (kw < 2) __syncthreads();
      const uint32_t d4 = blk + lane * 16;
      const uint32_t d2 = blk + 512 + (lane & 15) * 16 + (lane >> 4) * (2 * W_SLOT);
      stsm4(d4, raw[0][0], raw[0][1], raw[0][2], raw[0][3]);
      stsm4(d4 + 2 * W_SLOT, raw[2][0], raw[2][1], raw[2][2], raw[2][3]);
      stsm4(d2, raw[0][4], raw[0][5], raw[2][4], raw[2][5]);
      uint32_t u1[6], u2[6];
#pragma unroll
      for (int j = 0; j < 6; ++j) {
        const float tl = bf_lo(raw[0][j]) + bf_lo(raw[2][j]), th = bf_hi(raw[0][j]) + bf_hi(raw[2][j]);
        const float ml = bf_lo(raw[1][j]), mh = bf_hi(raw[1][j]);
        u1[j] = pack_bf16(tl + ml, th + mh);
        u2[j] = pack_bf16(tl - ml, th - mh);
      }
      stsm4(d4 + W_SLOT, u1[0], u1[1], u1[2], u1[3]);
      stsm4(d4 + 3 * W_SLOT, u2[0], u2[1], u2[2], u2[3]);
      stsm4(d2 + W_SLOT, u1[4], u1[5], u2[4], u2[5]);
    }
    proxy_fence();
  }
  asm volatile("barrier.cluster.wait.aligned;" ::: "memory");
  __syncthreads();

  if (warp >= 8) {
    asm volatile("setmaxnreg.dec.sync.aligned.u32 24;");
    if (warp < 10) {
      const int w = warp - 8, o = w ^ 1, dir = 1 - 2 * o;
      const int ybase = seg0 + o * (4 * NB - 1);
      uint32_t peer_free;
      asm volatile("mapa.shared::cluster.u32 %0, %1, %2;" : "=r"(peer_free) : "r"(bars + 32 + 16 * w), "r"(half ^ 1));
      auto fill = [&](int wg, int t, int y, int dy) {
        const uint32_t dst = sbase + wg * RING_BYTES + ((t + 1) & 1) * STAGE_BYTES, fb = bars + wg * 16 + ((t + 1) & 1) * 8;
        if (elect_one()) {
          mbar_expect_tx(fb, 2 * ROW_TX);
          tma_row(dst, &xmap, line0, y, fb);
          tma_row(dst + ROW_PITCH, &xmap, line0, y + dy, fb);
        }
      };
      if (w == 0) fill(1, 0, ybase, dir);
      else if (elect_one()) tma_row_prefetch(&xmap, line0, seg0 + 2 + half);
#pragma unroll 1
      for (int t = 0; t < NB; ++t) {
        mbar_wait(bars + w * 16 + ((t + 1) & 1) * 8, ((t + 1) >> 1) & 1);
        asm volatile("bar.sync %0, 288;" ::"r"(2 - w) : "memory");
        if (t + w == 0) fill(0, 1, seg0 + 2, 1);
        const int tn = t + 1 + w;
        if (tn < NB) {
          const uint32_t dst = sbase + o * RING_BYTES + ((tn + 1) & 1) * STAGE_BYTES, fb = bars + o * 16 + ((tn + 1) & 1) * 8;
          if (elect_one()) {
            mbar_expect_tx(fb, 2 * ROW_TX);
            asm volatile("mbarrier.arrive.relaxed.cluster.shared::cluster.b64 _, [%0];" ::"r"(peer_free + (t & 1) * 8) : "memory");
          }
          mbar_wait(bars + 32 + 16 * w + (t & 1) * 8, (t >> 1) & 1);
          if (elect_one()) tma_row_both(dst + half * ROW_PITCH, &xmap, line0, ybase + dir * (2 * tn + half), fb);
        }
        if (tn >= PF_START && tn + PF_DIST < NB && elect_one()) tma_row_prefetch(&xmap, line0, ybase + dir * (2 * (tn + PF_DIST) + half));
      }
      if (w == 0) asm volatile("bar.arrive 2, 288;" ::: "memory");
    }
  } else {
    asm volatile("setmaxnreg.inc.sync.aligned.u32 240;");
    const int wg = warp >> 2, w = warp & 3;
    const int g = lane >> 2, t4 = lane & 3;

    uint32_t la[12];
#pragma unroll
    for (int q = 0; q < 3; ++q)
      asm volatile("ld.shared.v4.b32 {%0,%1,%2,%3}, [%4];" : "=r"(la[4 * q]), "=r"(la[4 * q + 1]), "=r"(la[4 * q + 2]), "=r"(la[4 * q + 3])
                   : "r"(sbase + LA_OFF + q * 2048 + (tid & 127) * 16) : "memory");
    uint32_t soff = wg * RING_BYTES;
    float b2[12];
    {
      const uint32_t r[6] = {bias_v.x, bias_v.y, bias_v.z, bias_v.w, bias_u.x, bias_u.y};
#pragma unroll
      for (int j = 0; j < 6; ++j) { b2[2 * j] = 2.f * bf_lo(r[j]); b2[2 * j + 1] = 2.f * bf_hi(r[j]); }
    }
    const int orow = wg ? -OROW : OROW;
    uint64_t op16 = (uint64_t)__cvta_generic_to_global(out) + (ptrdiff_t)(seg0 + wg * (4 * NB - 1)) * OROW - (ptrdiff_t)orow
                    + ((pair & 7) * 64 + 16 * w + 2 * g) * (CH * 2) + off64 + 16 * t4;
    uint64_t op8 = op16 + (int64_t)(off32 - off64 - 8 * t4);
    op16 -= 2 * (int64_t)orow; op8 -= 2 * (int64_t)orow;
    uint64_t oq16 = op16 + orow, oq8 = op8 + orow;
    const int64_t ostep = 2 * (int64_t)orow;
    auto advance = [&](uint64_t& p) { asm volatile("add.s64 %0, %0, %1;" : "+l"(p) : "l"(ostep)); };
    const uint64_t dswap = wg ? (uint64_t)((2 * W_SLOT) >> 4) : 0;

    constexpr int NAB = LDA + 2;
    float Z0[24], Z1[24], Z2[24], Z3[24];
    uint32_t A[NAB][4], B[NAB][4], S[3][4], D[3][4], MP[3][4], MQ[3][4];
    auto store = [&](const uint32_t (&y)[12], int n, int on, uint64_t p16, uint64_t p8) {
      if (n == 0) st128<0>(p16, on, y[0], y[1], y[2], y[3]);
      if (n == 1) st128<192>(p16, on, y[6], y[7], y[8], y[9]);
      if (n == 2) st64<0>(p8, on, y[4], y[5]);
      if (n == 3) st64<192>(p8, on, y[10], y[11]);
    };
    auto load = [&](int cg) { ldsm4(A[cg % NAB], la[cg] + soff); ldsm4(B[cg % NAB], la[cg] + soff + ROW_PITCH); };
    const uint32_t vzero = __shfl_sync(0xffffffffu, (uint32_t)tid & zero2, lane);
    const uint32_t gate_tx = vzero + 1 + wg;
    uint32_t clk = 0;
    auto prep = [&](int r) {
#pragma unroll
      for (int i = 0; i < 4; ++i) {
        const int src = ((r - 1) & ~1) + (i >> 1), k = 1 + (i & 1);
        if (r < 12) S[r % 3][i] = hadd2(A[r % NAB][i], B[r % NAB][i]);
        if (r > 0) MP[r % 3][i] = copy32((r & 1) ? A[src % NAB][k] : S[src % 3][k], zero2);
        if (r < 12) D[r % 3][i] = hsub2(A[r % NAB][i], B[r % NAB][i]);
        if (r > 0) {
          const uint32_t v = (r & 1) ? B[src % NAB][k] : D[src % 3][k];
          if (i == 3 && r >= 2) asm volatile("lop3.b32 %0, %1, %2, %3, 0xF8;" : "=r"(MQ[r % 3][i]) : "r"(v), "r"(clk), "r"(vzero));
          else MQ[r % 3][i] = copy32(v, zero2);
        }
      }
    };

    mbar_wait(bars + wg * 16, 0);
    {
      uint32_t F[12][4], M[6][4];
      const uint64_t d3 = WDESC + dswap + zero2;
      if (wg == 1) asm volatile("bar.sync 3, 256;" ::: "memory");
#pragma unroll
      for (int cg = 0; cg < 12; ++cg) ldsm4(F[cg], la[cg] + (wg ? 0 : ROW_PITCH));
      if (wg == 0) asm volatile("bar.arrive 3, 256;" ::: "memory");
      else asm volatile("bar.arrive 2, 288;" ::: "memory");
#pragma unroll
      for (int c = 0; c < 6; ++c) {
        M[c][0] = copy32(F[2 * c][1], zero2); M[c][1] = copy32(F[2 * c][2], zero2);
        M[c][2] = copy32(F[2 * c + 1][1], zero2); M[c][3] = copy32(F[2 * c + 1][2], zero2);
        wg_fence();
        if (c == 0) mma48<0>(Z3, F[0], d3, d_outer(0, 3));
        else mma48<1>(Z3, F[2 * c], d3, d_outer(2 * c, 3));
        mma48<1>(Z3, F[2 * c + 1], d3, d_outer(2 * c + 1, 3));
        mma48<1>(Z3, M[c], d3, d_mid(c, 3));
      }
      wg_commit();
    }
    wg_wait<0>();
    pin(Z3);
#pragma unroll
    for (int i = 0; i < 24; ++i) {
      Z0[i] = 0.f;
      Z1[i] = Z3[i] + b2[(i >> 2) * 2 + (i & 1)];
      Z2[i] = -Z3[i];
    }
#pragma unroll
    for (int i = 0; i < 4; ++i) { A[11 % NAB][i] = 0; B[11 % NAB][i] = 0; S[11 % 3][i] = 0; D[11 % 3][i] = 0; MP[12 % 3][i] = 0; MQ[12 % 3][i] = 0; }

    for (int t = 0; t < NB; ++t) {
      uint32_t yo[12], ye[12];
#pragma unroll
      for (int i = 0; i < 4; ++i) {
        yo[i] = A[11 % NAB][i]; yo[6 + i] = B[11 % NAB][i]; ye[i] = S[11 % 3][i]; ye[6 + i] = D[11 % 3][i];
        yo[4 + (i & 1) + 6 * (i >> 1)] = MP[12 % 3][i]; ye[4 + (i & 1) + 6 * (i >> 1)] = MQ[12 % 3][i];
      }
      auto block = [&](int k) {
        if (t > (int)((k & 1) ? zero : zero2)) {
          float ev[2];
#pragma unroll
          for (int u = 0; u < 2; ++u) {
            const int e = k / 6, j = k % 6, i = 4 * j + 2 * e + u;
            if (u == 0) yo[k] = pack_bf16(Z0[i], Z0[i + 1]);
            const float sm = Z1[i] + Z2[i], df = Z1[i] - Z2[i];
            const float p = fmaf(0.5f, sm, -Z0[i]);
            ev[u] = fmaf(0.5f, df, -Z3[i]);
            Z0[i] = p;
            Z1[i] = (p + b2[2 * j + u]) + Z3[i];
            Z2[i] = p - Z3[i];
            if (u == 1) ye[k] = pack_bf16(ev[0], ev[1]);
            if (j == 3 && u == 0) store(yo, e, t - 1, op16, op8);
            if (j == 4 && u == 0) store(ye, e, 1, oq16, oq8);
            if (j == 5 && u == 0) store(yo, 2 + e, t - 1, op16, op8);
            if (j == 5 && u == 1) store(ye, 2 + e, 1, oq16, oq8);
            if (k == 0 && u == 0) { advance(op16); advance(op8); }
            if (k == 1 && u == 0) { advance(oq16); advance(oq8); }
          }
        }
      };
      if (t > 0) {
#pragma unroll
        for (int k = 0; k < 10; ++k) block(k);
      }
      soff = wg * RING_BYTES + ((t + 1) & 1) * STAGE_BYTES;
      if (wg) asm volatile("bar.sync 1, 288;" ::: "memory"); else asm volatile("bar.sync 2, 288;" ::: "memory");
      load(0);
      block(10);
      load(1);
      block(11);
      load(2);
      prep(0);
      const uint64_t dbase = WDESC + (uint64_t)(t & zero), db0 = dbase - dswap, db3 = dbase + dswap;
      wg_fence();
#pragma unroll
      for (int r = 0; r < 13; ++r) {
        if (r < 12) {
          mma48<1>(Z0, A[r % NAB], db0, d_outer(r, 0));
          mma48<1>(Z1, S[r % 3], dbase, d_outer(r, 1));
          mma48<1>(Z2, D[r % 3], dbase, d_outer(r, 2));
          if (r == 0) mma48<0>(Z3, B[r % NAB], db3, d_outer(r, 3));
          else mma48<1>(Z3, B[r % NAB], db3, d_outer(r, 3));
        }
        if (r > 0) {
          const int c = (r - 1) >> 1;
          if (r & 1) { mma48<1>(Z0, MP[r % 3], db0, d_mid(c, 0)); mma48<1>(Z3, MQ[r % 3], db3, d_mid(c, 3)); }
          else       { mma48<1>(Z1, MP[r % 3], dbase, d_mid(c, 1)); mma48<1>(Z2, MQ[r % 3], dbase, d_mid(c, 2)); }
        }
        wg_commit();
        if (r + LDA < 12) load(r + LDA);
        static_assert(LDA == 3 && GATE_R + LDA >= 11, "the gate arrival doubles as the stage release");
        if (r == GATE_R) asm volatile("bar.arrive %0, 288;" ::"r"(gate_tx) : "memory");
        if (r < 12) {
          prep(r + 1);
          wg_fence();
          wg_wait<1>();
          if (r < 11) asm volatile("mov.u32 %0, %clock;" : "=r"(clk) :: "memory");
        } else {
          wg_wait<0>();
        }
      }
      pin(Z0); pin(Z1); pin(Z2); pin(Z3);
    }
    advance(op16); advance(op8);
    if (wg == 0) asm volatile("bar.arrive 2, 288;" ::: "memory");

    {
      const uint32_t xch = sbase + STAGE_BYTES + (tid & 127) * 16;
      uint32_t yo[12], ye[12], y2[12], y3[12];
#pragma unroll
      for (int k = 0; k < 12; ++k) yo[k] = pack_bf16(Z0[4 * (k % 6) + 2 * (k / 6)], Z0[4 * (k % 6) + 2 * (k / 6) + 1]);
#pragma unroll
      for (int n = 0; n < 4; ++n) store(yo, n, 1, op16, op8);
#pragma unroll
      for (int j = 0; j < 6; ++j) {
        sched_fence();
        float ev[4];
#pragma unroll
        for (int u = 0; u < 4; ++u) {
          const int i = 4 * j + u;
          ev[u] = fmah(fsub(Z1[i], Z2[i]), Z3[i]);
          Z0[i] = fmah(fadd(Z1[i], Z2[i]), Z0[i]);
        }
        ye[j] = pack_bf16(ev[0], ev[1]); ye[6 + j] = pack_bf16(ev[2], ev[3]);
        asm volatile("{\n.reg .pred p;\nsetp.le.s32 p, %5, 0;\n@p st.shared.v4.f32 [%4], {%0,%1,%2,%3};\n}\n"
                     ::"f"(Z0[4 * j]), "f"(Z0[4 * j + 1]), "f"(Z0[4 * j + 2]), "f"(Z0[4 * j + 3]), "r"(xch + j * 4096), "r"(wg + zero) : "memory");
        asm volatile("{\n.reg .pred p;\nsetp.le.s32 p, %5, 0;\n@p st.shared.v4.f32 [%4], {%0,%1,%2,%3};\n}\n"
                     ::"f"(Z3[4 * j]), "f"(Z3[4 * j + 1]), "f"(Z3[4 * j + 2]), "f"(Z3[4 * j + 3]), "r"(xch + j * 4096 + 2048), "r"(wg + zero2) : "memory");
        if (j == 3) { store(ye, 0, 1, op16 + orow, op8 + orow); store(ye, 1, 1, op16 + orow, op8 + orow); }
        if (j == 5) { store(ye, 2, 1, op16 + orow, op8 + orow); store(ye, 3, 1, op16 + orow, op8 + orow); }
      }
      if (wg == 0) asm volatile("bar.arrive 3, 256;" ::: "memory");
      else asm volatile("bar.sync 3, 256;" ::: "memory");
#pragma unroll
      for (int j = 0; j < 6; ++j) {
        asm volatile("{\n.reg .pred p;\nsetp.gt.s32 p, %5, 0;\n@p ld.shared.v4.f32 {%0,%1,%2,%3}, [%4];\n}\n"
                     : "+f"(Z1[4 * j]), "+f"(Z1[4 * j + 1]), "+f"(Z1[4 * j + 2]), "+f"(Z1[4 * j + 3]) : "r"(xch + j * 4096), "r"(wg + zero) : "memory");
        asm volatile("{\n.reg .pred p;\nsetp.gt.s32 p, %5, 0;\n@p ld.shared.v4.f32 {%0,%1,%2,%3}, [%4];\n}\n"
                     : "+f"(Z2[4 * j]), "+f"(Z2[4 * j + 1]), "+f"(Z2[4 * j + 2]), "+f"(Z2[4 * j + 3]) : "r"(xch + j * 4096 + 2048), "r"(wg + zero2) : "memory");
      }
#pragma unroll
      for (int j = 0; j < 6; ++j) {
        if (j == 2 || j == 4) sched_fence();
#pragma unroll
        for (int e = 0; e < 2; ++e) {
          const int i = 4 * j + 2 * e;
          y2[6 * e + j] = pack_bf16(fadd(Z0[i], Z2[i]), fadd(Z0[i + 1], Z2[i + 1]));
          y3[6 * e + j] = pack_bf16(fadd(Z3[i], Z1[i]), fadd(Z3[i + 1], Z1[i + 1]));
        }
        if (j == 3 || j == 5) {
#pragma unroll
          for (int n = j - 3; n < j - 1; ++n) {
            store(y2, n, wg + zero, op16 + 2 * orow, op8 + 2 * orow);
            store(y3, n, wg + zero2, op16 + 3 * orow, op8 + 3 * orow);
          }
        }
      }
    }
  }
}

typedef CUresult (*EncodeTiledFn)(CUtensorMap*, CUtensorMapDataType, cuuint32_t, void*, const cuuint64_t*,
                                  const cuuint64_t*, const cuuint32_t*, const cuuint32_t*, CUtensorMapInterleave,
                                  CUtensorMapSwizzle, CUtensorMapL2promotion, CUtensorMapFloatOOBfill);

}

extern "C" void kernel_launch(void* const* d_in, const int* in_sizes, int n_in, void* d_out, int out_size) {
  (void)in_sizes; (void)n_in; (void)out_size;
  static EncodeTiledFn encode = nullptr;
  if (!encode) {
    void* fn = nullptr;
    cudaDriverEntryPointQueryResult qr;
    cudaGetDriverEntryPoint("cuTensorMapEncodeTiled", &fn, cudaEnableDefault, &qr);
    encode = (EncodeTiledFn)fn;
    cudaFuncSetAttribute(conv3x3_kernel, cudaFuncAttributeMaxDynamicSharedMemorySize, SMEM_BYTES);
  }
  CUtensorMap xmap;
  const cuuint64_t dims[3] = {64, (cuuint64_t)(OROW / 128), (cuuint64_t)IMG_H};
  const cuuint64_t strides[2] = {128, (cuuint64_t)OROW};
  const cuuint32_t box[3] = {64, ROW_LINES, 1};
  const cuuint32_t estr[3] = {1, 1, 1};
  encode(&xmap, CU_TENSOR_MAP_DATA_TYPE_BFLOAT16, 3, d_in[0], dims, strides, box, estr, CU_TENSOR_MAP_INTERLEAVE_NONE,
         CU_TENSOR_MAP_SWIZZLE_128B, CU_TENSOR_MAP_L2_PROMOTION_L2_256B, CU_TENSOR_MAP_FLOAT_OOB_FILL_NONE);
  conv3x3_kernel<<<128, NUM_THREADS, SMEM_BYTES, cudaStreamPerThread>>>(
      xmap, (const uint8_t*)d_in[1], (const __nv_bfloat16*)d_in[2], (__nv_bfloat16*)d_out, 0u, 0u);
}
```

```cpp
#include <cuda_runtime.h>
#include <cuda_bf16.h>
#include <cuda.h>
#include <stdint.h>

#define DEVI __device__ __forceinline__

namespace {

constexpr int IMG_H = 512, IMG_W = 512, CH = 96;
constexpr int OROW = IMG_W * CH * 2;
constexpr int NB = 16;
constexpr int ROW_LINES = 100;
constexpr int ROW_TX = ROW_LINES * 128;
constexpr int ROW_PITCH = 13312;
constexpr int STAGE_BYTES = 2 * ROW_PITCH;
constexpr int RING_BYTES = 2 * STAGE_BYTES;
constexpr int W_TAP = CH * CH * 2;
constexpr int W_RAW = 3 * W_TAP;
constexpr int W_OFF = RING_BYTES + W_RAW;
constexpr int W_SLOT = CH * 48 * 2;
constexpr int W_KW = 4 * W_SLOT;
constexpr int BAR_OFF = W_OFF + 3 * W_KW;
constexpr int LA_OFF = BAR_OFF + 128;
constexpr int XCH_OFF = LA_OFF;
constexpr int SMEM_BYTES = XCH_OFF + 12288;
constexpr uint32_t SMEM_BASE = 1024;
constexpr int NUM_THREADS = 384;
constexpr int LDA = 3;
constexpr int GATE_R = 8;
constexpr int PF_START = 3, PF_DIST = 2;

constexpr uint64_t WDESC = (uint64_t)((SMEM_BASE + W_OFF) >> 4) | ((uint64_t)(128 >> 4) << 32);
__host__ __device__ constexpr int w_slot(int pos) { return pos == 0 ? 2 : pos == 1 ? 1 : pos == 2 ? 3 : 0; }
__host__ __device__ constexpr uint32_t d_outer(int cg, int pos) { return (uint32_t)(((w_slot(pos) * W_SLOT + cg * 768) >> 4) | (((2 * W_KW) >> 4) << 16)); }
__host__ __device__ constexpr uint32_t d_mid(int c, int pos) { return (uint32_t)(((W_KW + w_slot(pos) * W_SLOT + c * 1536) >> 4) | ((768 >> 4) << 16)); }

DEVI uint32_t smem_u32(const void* p) { return (uint32_t)__cvta_generic_to_shared(p); }
DEVI void wg_fence() { asm volatile("wgmma.fence.sync.aligned;" ::: "memory"); }
DEVI void wg_commit() { asm volatile("wgmma.commit_group.sync.aligned;" ::: "memory"); }
template <int N> DEVI void wg_wait() { asm volatile("wgmma.wait_group.sync.aligned %0;" ::"n"(N) : "memory"); }
DEVI void proxy_fence() { asm volatile("fence.proxy.async.shared::cta;" ::: "memory"); }
DEVI void sched_fence() { asm volatile("pmevent 0;" ::: "memory"); }

DEVI void ldsm4(uint32_t (&r)[4], uint32_t addr) {
  asm volatile("ldmatrix.sync.aligned.m8n8.x4.shared.b16 {%0,%1,%2,%3}, [%4];"
               : "=r"(r[0]), "=r"(r[1]), "=r"(r[2]), "=r"(r[3]) : "r"(addr) : "memory");
}
DEVI void stsm4(uint32_t addr, uint32_t r0, uint32_t r1, uint32_t r2, uint32_t r3) {
  asm volatile("stmatrix.sync.aligned.m8n8.x4.shared.b16 [%0], {%1,%2,%3,%4};"
               ::"r"(addr), "r"(r0), "r"(r1), "r"(r2), "r"(r3) : "memory");
}
DEVI uint32_t hadd2(uint32_t a, uint32_t b) { uint32_t r; asm volatile("add.rn.bf16x2 %0, %1, %2;" : "=r"(r) : "r"(a), "r"(b)); return r; }
DEVI uint32_t hsub2(uint32_t a, uint32_t b) { uint32_t r; asm volatile("sub.rn.bf16x2 %0, %1, %2;" : "=r"(r) : "r"(a), "r"(b)); return r; }
DEVI uint32_t copy32(uint32_t a, uint32_t z) { uint32_t r; asm volatile("or.b32 %0, %1, %2;" : "=r"(r) : "r"(a), "r"(z)); return r; }
DEVI uint32_t pack_bf16(float lo, float hi) { uint32_t r; asm("cvt.rn.bf16x2.f32 %0, %1, %2;" : "=r"(r) : "f"(hi), "f"(lo)); return r; }
DEVI float fadd(float a, float b) { float r; asm volatile("add.rn.f32 %0, %1, %2;" : "=f"(r) : "f"(a), "f"(b)); return r; }
DEVI float fsub(float a, float b) { float r; asm volatile("sub.rn.f32 %0, %1, %2;" : "=f"(r) : "f"(a), "f"(b)); return r; }
DEVI float fmah(float a, float b) { float r; asm volatile("fma.rn.f32 %0, %1, 0f3F000000, %2;" : "=f"(r) : "f"(a), "f"(-b)); return r; }
DEVI float bf_lo(uint32_t v) { return __uint_as_float(v << 16); }
DEVI float bf_hi(uint32_t v) { return __uint_as_float(v & 0xffff0000u); }

DEVI void mbar_init(uint32_t bar, uint32_t cnt) { asm volatile("mbarrier.init.shared::cta.b64 [%0], %1;" ::"r"(bar), "r"(cnt) : "memory"); }
DEVI void mbar_expect_tx(uint32_t bar, uint32_t tx) { asm volatile("mbarrier.arrive.expect_tx.shared::cta.b64 _, [%0], %1;" ::"r"(bar), "r"(tx) : "memory"); }
DEVI void mbar_wait(uint32_t bar, uint32_t parity) {
  asm volatile(
      "{\n.reg .pred p;\n.reg .u32 c;\n"
      "mbarrier.try_wait.parity.shared::cta.b64 p, [%0], %1;\n"
      "@p bra.uni DONE;\n"
      "mov.u32 c, 0;\n"
      "SPIN:\n"
      "mbarrier.try_wait.parity.shared::cta.b64 p, [%0], %1, 100000;\n"
      "@p bra.uni DONE;\n"
      "add.u32 c, c, 1;\n"
      "setp.lt.u32 p, c, 0x4000;\n"
      "@p bra.uni SPIN;\n"
      "DONE:\n}\n" ::"r"(bar), "r"(parity) : "memory");
}
DEVI bool elect_one() {
  uint32_t p;
  asm volatile("{\n.reg .pred p;\nelect.sync _|p, 0xffffffff;\nselp.b32 %0, 1, 0, p;\n}\n" : "=r"(p));
  return p != 0;
}
DEVI void tma_row(uint32_t dst, const CUtensorMap* map, int line, int y, uint32_t bar) {
  asm volatile("cp.async.bulk.tensor.3d.shared::cluster.global.mbarrier::complete_tx::bytes [%0], [%1, {%3, %4, %5}], [%2];"
               ::"r"(dst), "l"(map), "r"(bar), "r"(0), "r"(line), "r"(y) : "memory");
}
DEVI void tma_row_both(uint32_t dst, const CUtensorMap* map, int line, int y, uint32_t bar) {
  asm volatile("cp.async.bulk.tensor.3d.shared::cluster.global.mbarrier::complete_tx::bytes.multicast::cluster [%0], [%1, {%3, %4, %5}], [%2], %6;"
               ::"r"(dst), "l"(map), "r"(bar), "r"(0), "r"(line), "r"(y), "h"((uint16_t)3) : "memory");
}
DEVI void tma_row_prefetch(const CUtensorMap* map, int line, int y) {
  asm volatile("cp.async.bulk.prefetch.tensor.3d.L2.global [%0, {%1, %2, %3}];" ::"l"(map), "r"(0), "r"(line), "r"(y) : "memory");
}
DEVI void bulk_load(uint32_t dst, const void* src, uint32_t bytes, uint32_t bar) {
  asm volatile("cp.async.bulk.shared::cluster.global.mbarrier::complete_tx::bytes [%0], [%1], %2, [%3];"
               ::"r"(dst), "l"(src), "r"(bytes), "r"(bar) : "memory");
}

template <int ACC>
DEVI void mma48(float (&d)[24], const uint32_t (&a)[4], uint64_t dbase, uint32_t doff) {
  const uint64_t desc = dbase + (uint64_t)doff;
  asm volatile(
      "wgmma.mma_async.sync.aligned.m64n48k16.f32.bf16.bf16 "
      "{%0,%1,%2,%3,%4,%5,%6,%7,%8,%9,%10,%11,%12,%13,%14,%15,%16,%17,%18,%19,%20,%21,%22,%23}, "
      "{%24,%25,%26,%27}, %28, %29, 1, 1, 1;\n"
      : "+f"(d[0]), "+f"(d[1]), "+f"(d[2]), "+f"(d[3]), "+f"(d[4]), "+f"(d[5]), "+f"(d[6]), "+f"(d[7]),
        "+f"(d[8]), "+f"(d[9]), "+f"(d[10]), "+f"(d[11]), "+f"(d[12]), "+f"(d[13]), "+f"(d[14]), "+f"(d[15]),
        "+f"(d[16]), "+f"(d[17]), "+f"(d[18]), "+f"(d[19]), "+f"(d[20]), "+f"(d[21]), "+f"(d[22]), "+f"(d[23])
      : "r"(a[0]), "r"(a[1]), "r"(a[2]), "r"(a[3]), "l"(desc), "n"(ACC));
}
DEVI void pin(float (&d)[24]) {
#pragma unroll
  for (int i = 0; i < 24; ++i) asm volatile("" : "+f"(d[i]) :: "memory");
}

template <int OFF>
DEVI void st128(uint64_t p, int on, uint32_t a, uint32_t b, uint32_t c, uint32_t d) {
  asm volatile("{\n.reg .pred p;\nsetp.gt.s32 p, %5, 0;\n@p st.global.v4.b32 [%0+%6], {%1,%2,%3,%4};\n}\n"
               ::"l"(p), "r"(a), "r"(b), "r"(c), "r"(d), "r"(on), "n"(OFF) : "memory");
}
template <int OFF>
DEVI void st64(uint64_t p, int on, uint32_t a, uint32_t b) {
  asm volatile("{\n.reg .pred p;\nsetp.gt.s32 p, %3, 0;\n@p st.global.v2.b32 [%0+%4], {%1,%2};\n}\n"
               ::"l"(p), "r"(a), "r"(b), "r"(on), "n"(OFF) : "memory");
}

__global__ void __cluster_dims__(2, 1, 1) __launch_bounds__(NUM_THREADS, 1)
conv3x3_kernel(const __grid_constant__ CUtensorMap xmap, const uint8_t* __restrict__ xin, const uint8_t* __restrict__ wgt,
               const __nv_bfloat16* __restrict__ bias, __nv_bfloat16* __restrict__ out, uint32_t zero, uint32_t zero2) {
  extern __shared__ __align__(1024) uint8_t smem_raw[];
  if (threadIdx.x < 11) asm volatile("prefetch.global.L2 [%0];" ::"l"(wgt + min((blockIdx.x * 11 + threadIdx.x) * 128, 3 * W_RAW - 128)));
  const uint32_t sbase = smem_u32(smem_raw);
  const uint32_t bars = sbase + BAR_OFF;
  const int tid = threadIdx.x, warp = __shfl_sync(0xffffffffu, tid >> 5, 0), lane = tid & 31;
  const int half = blockIdx.x & 1, pair = blockIdx.x >> 1;
  const int off64 = half * 128, off32 = 64 + half * 32;
  const int line0 = (pair & 7) * 96 - 2, mid = (pair >> 3) * (4 * NB) + 2 * NB;

  if (warp == 11) {
    if (elect_one()) {
#pragma unroll
      for (int kw = 0; kw < 3; ++kw) mbar_init(bars + 64 + 8 * kw, 1);
      proxy_fence();
#pragma unroll
      for (int kw = 0; kw < 3; ++kw) {
        mbar_expect_tx(bars + 64 + 8 * kw, W_RAW);
#pragma unroll
        for (int kh = 0; kh < 3; ++kh)
          bulk_load(sbase + RING_BYTES + ((kw + 1) % 3) * W_RAW + kh * W_TAP, wgt + (kh * 3 + kw) * W_TAP, W_TAP, bars + 64 + 8 * kw);
      }
      sched_fence();
#pragma unroll
      for (int i = 0; i < 8; ++i) mbar_init(bars + 8 * i, 1);
      asm volatile("fence.mbarrier_init.release.cluster;" ::: "memory");
      proxy_fence();
      mbar_expect_tx(bars, 2 * ROW_TX);
      tma_row(sbase, &xmap, line0, mid, bars);
      tma_row(sbase + ROW_PITCH, &xmap, line0, mid + 1, bars);
    }
  }
  if ((sbase & 0xFFFFFFu) != SMEM_BASE) __trap();
  const uint4 bias_v = __ldg(reinterpret_cast<const uint4*>(bias + off64 / 2 + 8 * (lane & 3)));
  const uint2 bias_u = __ldg(reinterpret_cast<const uint2*>(bias + off32 / 2 + 4 * (lane & 3)));
  __syncthreads();
  if (tid >= 128 && tid < 328) {
    const int k = tid >= 228, line = line0 + tid - 128 - 100 * k;
    if (line >= 0 && line < OROW / 128) asm volatile("prefetch.global.L2 [%0];" ::"l"(xin + (size_t)(mid - 2 * k + half) * OROW + line * 128));
  }
  asm volatile("barrier.cluster.arrive.relaxed.aligned;" ::: "memory");
  {
    const int p = 16 * (warp & 3) + 2 * (lane & 7) - 1 + (lane >> 3);
    const uint32_t off = 192 * p + 256 + 64 * (warp >> 2), a0 = sbase + (off ^ (((off >> 7) & 7) << 4));
    asm volatile("st.shared.v4.b32 [%0], {%1,%2,%3,%4};" ::"r"(sbase + LA_OFF + tid * 16), "r"(a0), "r"(a0 ^ 16), "r"(a0 ^ 32), "r"(a0 ^ 48) : "memory");
  }
  {
    const int g = lane >> 2, t4 = lane & 3;
    uint32_t blk = sbase + W_OFF + warp * 768;
#pragma unroll 1
    for (int kw = 0; kw < 3; ++kw, blk += W_KW) {
      const uint32_t src = sbase + RING_BYTES + (kw == 2 ? 0 : kw + 1) * W_RAW + (warp * 8 + g) * 192;
      mbar_wait(bars + 64 + 8 * kw, 0);
      uint32_t raw[3][6];
#pragma unroll
      for (int kh = 0; kh < 3; ++kh) {
        asm volatile("ld.shared.v4.b32 {%0,%1,%2,%3}, [%4];" : "=r"(raw[kh][0]), "=r"(raw[kh][1]), "=r"(raw[kh][2]), "=r"(raw[kh][3])
                     : "r"(src + kh * W_TAP + off64 + 16 * t4) : "memory");
        asm volatile("ld.shared.v2.b32 {%0,%1}, [%2];" : "=r"(raw[kh][4]), "=r"(raw[kh][5])
                     : "r"(src + kh * W_TAP + off32 + 8 * t4) : "memory");
      }
      if (kw < 2) __syncthreads();
      const uint32_t d4 = blk + lane * 16;
      const uint32_t d2 = blk + 512 + (lane & 15) * 16 + (lane >> 4) * (2 * W_SLOT);
      stsm4(d4, raw[0][0], raw[0][1], raw[0][2], raw[0][3]);
      stsm4(d4 + 2 * W_SLOT, raw[2][0], raw[2][1], raw[2][2], raw[2][3]);
      stsm4(d2, raw[0][4], raw[0][5], raw[2][4], raw[2][5]);
      uint32_t u1[6], u2[6];
#pragma unroll
      for (int j = 0; j < 6; ++j) {
        const float tl = bf_lo(raw[0][j]) + bf_lo(raw[2][j]), th = bf_hi(raw[0][j]) + bf_hi(raw[2][j]);
        const float ml = bf_lo(raw[1][j]), mh = bf_hi(raw[1][j]);
        u1[j] = pack_bf16(tl + ml, th + mh);
        u2[j] = pack_bf16(tl - ml, th - mh);
      }
      stsm4(d4 + W_SLOT, u1[0], u1[1], u1[2], u1[3]);
      stsm4(d4 + 3 * W_SLOT, u2[0], u2[1], u2[2], u2[3]);
      stsm4(d2 + W_SLOT, u1[4], u1[5], u2[4], u2[5]);
    }
    proxy_fence();
  }
  asm volatile("barrier.cluster.wait.aligned;" ::: "memory");
  __syncthreads();

  if (warp >= 8) {
    asm volatile("setmaxnreg.dec.sync.aligned.u32 56;");
    if (warp < 10) {
      const int w = warp - 8, o = w ^ 1, dir = 1 - 2 * o;
      const int ybase = mid - o;
      uint32_t peer_free;
      asm volatile("mapa.shared::cluster.u32 %0, %1, %2;" : "=r"(peer_free) : "r"(bars + 32 + 16 * w), "r"(half ^ 1));
      if (elect_one()) {
        const uint32_t dst = sbase + o * RING_BYTES + w * STAGE_BYTES, fb = bars + o * 16 + w * 8;
        mbar_expect_tx(fb, 2 * ROW_TX);
        tma_row(dst, &xmap, line0, ybase + dir * 2 * w, fb);
        tma_row(dst + ROW_PITCH, &xmap, line0, ybase + dir * (2 * w + 1), fb);
      }
#pragma unroll 1
      for (int t = 0; t <= NB; ++t) {
        mbar_wait(bars + w * 16 + (t & 1) * 8, (t >> 1) & 1);
        if (t * w == 1) asm volatile("bar.sync 4, 96;" ::: "memory");
        asm volatile("bar.sync %0, 288;" ::"r"(2 - w) : "memory");
        const int tn = t + 1 + w;
        const uint32_t dst = sbase + o * RING_BYTES + (tn & 1) * STAGE_BYTES, fb = bars + o * 16 + (tn & 1) * 8;
        if (tn < NB) {
          if (elect_one()) {
            mbar_expect_tx(fb, 2 * ROW_TX);
            asm volatile("mbarrier.arrive.relaxed.cluster.shared::cluster.b64 _, [%0];" ::"r"(peer_free + (t & 1) * 8) : "memory");
          }
          mbar_wait(bars + 32 + 16 * w + (t & 1) * 8, (t >> 1) & 1);
          if (elect_one()) tma_row_both(dst + half * ROW_PITCH, &xmap, line0, ybase + dir * (2 * tn + half), fb);
        } else if (tn == NB && elect_one()) {
          mbar_expect_tx(fb, ROW_TX);
          tma_row(dst, &xmap, line0, ybase + dir * 2 * NB, fb);
        }
        if (tn >= PF_START && tn + PF_DIST < NB && elect_one()) tma_row_prefetch(&xmap, line0, ybase + dir * (2 * (tn + PF_DIST) + half));
      }
    } else {
      const int h = warp - 10;
      const uint32_t xch = sbase + XCH_OFF + lane * 16;
      uint32_t v[4][2][4];
      asm volatile("bar.sync 3, 192;" ::: "memory");
#pragma unroll
      for (int w = 0; w < 4; ++w) {
#pragma unroll
        for (int n = 0; n < 2; ++n) {
          asm volatile("ld.shared.v4.b32 {%0,%1,%2,%3}, [%4];" : "=r"(v[w][n][0]), "=r"(v[w][n][1]), "=r"(v[w][n][2]), "=r"(v[w][n][3])
                       : "r"(xch + (3 * h + n) * 2048 + w * 512) : "memory");
        }
      }
      asm volatile("bar.arrive 4, 96;" ::: "memory");
      asm volatile("bar.sync 3, 192;" ::: "memory");
      const uint64_t p16 = (uint64_t)__cvta_generic_to_global(out) + (size_t)(mid - h) * OROW + ((pair & 7) * 64 + 2 * (lane >> 2)) * (CH * 2) + off64 + 16 * (lane & 3);
      const uint64_t p8 = p16 + (int64_t)(off32 - off64 - 8 * (lane & 3));
#pragma unroll
      for (int w = 0; w < 4; ++w) {
#pragma unroll
        for (int n = 0; n < 3; ++n) {
          __nanosleep(400);
          uint32_t a, b, c, d, q[4];
          if (n < 2) {
            asm volatile("ld.shared.v4.b32 {%0,%1,%2,%3}, [%4];" : "=r"(a), "=r"(b), "=r"(c), "=r"(d) : "r"(xch + (3 * (1 - h) + n) * 2048 + w * 512) : "memory");
            q[0] = v[w][n & 1][0]; q[1] = v[w][n & 1][1]; q[2] = v[w][n & 1][2]; q[3] = v[w][n & 1][3];
          } else {
            asm volatile("ld.shared.v4.b32 {%0,%1,%2,%3}, [%4];" : "=r"(a), "=r"(b), "=r"(c), "=r"(d) : "r"(sbase + ROW_TX + (w + 4 * (1 - h)) * ROW_PITCH + lane * 16) : "memory");
            asm volatile("ld.shared.v4.b32 {%0,%1,%2,%3}, [%4];" : "=r"(q[0]), "=r"(q[1]), "=r"(q[2]), "=r"(q[3]) : "r"(xch + (3 * h + 2) * 2048 + w * 512) : "memory");
          }
          a = hadd2(a, q[0]); b = hadd2(b, q[1]); c = hadd2(c, q[2]); d = hadd2(d, q[3]);
          if (n == 0) st128<0>(p16 + w * 3072, 1, a, b, c, d);
          if (n == 1) st128<192>(p16 + w * 3072, 1, a, b, c, d);
          if (n == 2) { st64<0>(p8 + w * 3072, 1, a, b); st64<192>(p8 + w * 3072, 1, c, d); }
        }
      }
    }
  } else {
    asm volatile("setmaxnreg.inc.sync.aligned.u32 224;");
    const int wg = warp >> 2, w = warp & 3;
    const int g = lane >> 2, t4 = lane & 3;

    uint32_t la[12];
#pragma unroll
    for (int q = 0; q < 3; ++q)
      asm volatile("ld.shared.v4.b32 {%0,%1,%2,%3}, [%4];" : "=r"(la[4 * q]), "=r"(la[4 * q + 1]), "=r"(la[4 * q + 2]), "=r"(la[4 * q + 3])
                   : "r"(sbase + LA_OFF + q * 2048 + (tid & 127) * 16) : "memory");
    uint32_t soff = wg * RING_BYTES;
    float b2[12];
    {
      const uint32_t r[6] = {bias_v.x, bias_v.y, bias_v.z, bias_v.w, bias_u.x, bias_u.y};
#pragma unroll
      for (int j = 0; j < 6; ++j) { b2[2 * j] = 2.f * bf_lo(r[j]); b2[2 * j + 1] = 2.f * bf_hi(r[j]); }
    }
    const int orow = wg ? -OROW : OROW;
    uint64_t op16 = (uint64_t)__cvta_generic_to_global(out) + (ptrdiff_t)(mid - wg) * OROW - (ptrdiff_t)orow
                    + ((pair & 7) * 64 + 16 * w + 2 * g) * (CH * 2) + off64 + 16 * t4;
    uint64_t op8 = op16 + (int64_t)(off32 - off64 - 8 * t4);
    op16 -= 2 * (int64_t)orow; op8 -= 2 * (int64_t)orow;
    uint64_t oq16 = op16 + orow, oq8 = op8 + orow;
    const int64_t ostep = 2 * (int64_t)orow;
    auto advance = [&](uint64_t& p) { asm volatile("add.s64 %0, %0, %1;" : "+l"(p) : "l"(ostep)); };
    const uint64_t dswap = wg ? (uint64_t)((2 * W_SLOT) >> 4) : 0;

    constexpr int NAB = LDA + 2;
    float Z0[24], Z1[24], Z2[24], Z3[24];
    uint32_t A[NAB][4], B[NAB][4], S[3][4], D[3][4], MP[3][4], MQ[3][4];
    auto store = [&](const uint32_t (&y)[12], int n, int on, uint64_t p16, uint64_t p8) {
      if (n == 0) st128<0>(p16, on, y[0], y[1], y[2], y[3]);
      if (n == 1) st128<192>(p16, on, y[6], y[7], y[8], y[9]);
      if (n == 2) st64<0>(p8, on, y[4], y[5]);
      if (n == 3) st64<192>(p8, on, y[10], y[11]);
    };
    auto load = [&](int cg) { ldsm4(A[cg % NAB], la[cg] + soff); ldsm4(B[cg % NAB], la[cg] + soff + ROW_PITCH); };
    const uint32_t vzero = __shfl_sync(0xffffffffu, (uint32_t)tid & zero2, lane);
    uint32_t clk = 0;
    auto prep = [&](int r) {
#pragma unroll
      for (int i = 0; i < 4; ++i) {
        const int src = ((r - 1) & ~1) + (i >> 1), k = 1 + (i & 1);
        if (r < 12) S[r % 3][i] = hadd2(A[r % NAB][i], B[r % NAB][i]);
        if (r > 0) MP[r % 3][i] = copy32((r & 1) ? A[src % NAB][k] : S[src % 3][k], zero2);
        if (r < 12) D[r % 3][i] = hsub2(A[r % NAB][i], B[r % NAB][i]);
        if (r > 0) {
          const uint32_t v = (r & 1) ? B[src % NAB][k] : D[src % 3][k];
          if (i == 3 && r >= 2) asm volatile("lop3.b32 %0, %1, %2, %3, 0xF8;" : "=r"(MQ[r % 3][i]) : "r"(v), "r"(clk), "r"(vzero));
          else MQ[r % 3][i] = copy32(v, zero2);
        }
      }
    };

    if (wg == 1) asm volatile("bar.arrive 2, 288;" ::: "memory");
#pragma unroll
    for (int i = 0; i < 24; ++i) { Z0[i] = 0.f; Z1[i] = b2[(i >> 2) * 2 + (i & 1)]; Z2[i] = 0.f; Z3[i] = 0.f; }
#pragma unroll
    for (int i = 0; i < 4; ++i) { A[11 % NAB][i] = 0; B[11 % NAB][i] = 0; S[11 % 3][i] = 0; D[11 % 3][i] = 0; MP[12 % 3][i] = 0; MQ[12 % 3][i] = 0; }

    for (int t = 0; t < NB; ++t) {
      uint32_t yo[12], ye[12];
#pragma unroll
      for (int i = 0; i < 4; ++i) {
        yo[i] = A[11 % NAB][i]; yo[6 + i] = B[11 % NAB][i]; ye[i] = S[11 % 3][i]; ye[6 + i] = D[11 % 3][i];
        yo[4 + (i & 1) + 6 * (i >> 1)] = MP[12 % 3][i]; ye[4 + (i & 1) + 6 * (i >> 1)] = MQ[12 % 3][i];
      }
      auto block = [&](int k) {
        if (t > (int)((k & 1) ? zero : zero2)) {
          float ev[2];
#pragma unroll
          for (int u = 0; u < 2; ++u) {
            const int e = k / 6, j = k % 6, i = 4 * j + 2 * e + u;
            if (u == 0) yo[k] = pack_bf16(Z0[i], Z0[i + 1]);
            const float sm = Z1[i] + Z2[i], df = Z1[i] - Z2[i];
            const float p = fmaf(0.5f, sm, -Z0[i]);
            ev[u] = fmaf(0.5f, df, -Z3[i]);
            Z0[i] = p;
            Z1[i] = (p + b2[2 * j + u]) + Z3[i];
            Z2[i] = p - Z3[i];
            if (u == 1) ye[k] = pack_bf16(ev[0], ev[1]);
            if (j == 3 && u == 0) store(yo, e, t - 1, op16, op8);
            if (j == 4 && u == 0) store(ye, e, t - 1, oq16, oq8);
            if (j == 5 && u == 0) store(yo, 2 + e, t - 1, op16, op8);
            if (j == 5 && u == 1) store(ye, 2 + e, t - 1, oq16, oq8);
            if (k == 0 && u == 0) { advance(op16); advance(op8); }
            if (k == 1 && u == 0) { advance(oq16); advance(oq8); }
          }
        }
      };
      if (t > 0) {
#pragma unroll
        for (int k = 0; k < 10; ++k) block(k);
      }
      soff = wg * RING_BYTES + (t & 1) * STAGE_BYTES;
      if (wg) asm volatile("bar.sync 1, 288;" ::: "memory"); else asm volatile("bar.sync 2, 288;" ::: "memory");
      load(0);
      block(10);
      load(1);
      block(11);
      if (t == 1) {
        const uint32_t xch = sbase + XCH_OFF + (tid & 127) * 16;
        auto put = [&](int n, uint32_t a, uint32_t b, uint32_t c, uint32_t d) {
          asm volatile("st.shared.v4.b32 [%0], {%1,%2,%3,%4};" ::"r"(xch + n * 2048), "r"(a), "r"(b), "r"(c), "r"(d) : "memory");
        };
        put(0, ye[0], ye[1], ye[2], ye[3]); put(1, ye[6], ye[7], ye[8], ye[9]);
        put(3, yo[0], yo[1], yo[2], yo[3]); put(4, yo[6], yo[7], yo[8], yo[9]);
        const uint32_t x2 = wg ? sbase + ROW_TX + w * ROW_PITCH + lane * 16 : xch + 2 * 2048, x5 = x2 + (wg ? 4 * ROW_PITCH : 3 * 2048);
        asm volatile("st.shared.v4.b32 [%0], {%1,%2,%3,%4};" ::"r"(x2), "r"(ye[4]), "r"(ye[5]), "r"(ye[10]), "r"(ye[11]) : "memory");
        asm volatile("st.shared.v4.b32 [%0], {%1,%2,%3,%4};" ::"r"(x5), "r"(yo[4]), "r"(yo[5]), "r"(yo[10]), "r"(yo[11]) : "memory");
        asm volatile("bar.arrive 3, 192;" ::: "memory");
      }
      load(2);
      prep(0);
      const uint64_t dbase = WDESC + (uint64_t)(t & zero), db0 = dbase - dswap, db3 = dbase + dswap;
      wg_fence();
#pragma unroll
      for (int r = 0; r < 13; ++r) {
        if (r < 12) {
          mma48<1>(Z0, A[r % NAB], db0, d_outer(r, 0));
          mma48<1>(Z1, S[r % 3], dbase, d_outer(r, 1));
          mma48<1>(Z2, D[r % 3], dbase, d_outer(r, 2));
          if (r == 0) mma48<0>(Z3, B[r % NAB], db3, d_outer(r, 3));
          else mma48<1>(Z3, B[r % NAB], db3, d_outer(r, 3));
        }
        if (r > 0) {
          const int c = (r - 1) >> 1;
          if (r & 1) { mma48<1>(Z0, MP[r % 3], db0, d_mid(c, 0)); mma48<1>(Z3, MQ[r % 3], db3, d_mid(c, 3)); }
          else       { mma48<1>(Z1, MP[r % 3], dbase, d_mid(c, 1)); mma48<1>(Z2, MQ[r % 3], dbase, d_mid(c, 2)); }
        }
        wg_commit();
        if (r + LDA < 12) load(r + LDA);
        static_assert(LDA == 3 && GATE_R + LDA >= 11, "the gate arrival doubles as the stage release");
        if (r == GATE_R) asm volatile("bar.arrive %0, 288;" ::"r"(1 + wg) : "memory");
        if (r < 12) {
          prep(r + 1);
          wg_fence();
          wg_wait<1>();
          if (r < 11) asm volatile("mov.u32 %0, %clock;" : "=r"(clk) :: "memory");
        } else {
          wg_wait<0>();
        }
      }
      pin(Z0); pin(Z1); pin(Z2); pin(Z3);
    }
    advance(op16); advance(op8);

    {
      uint32_t yo[12], ye[12], F[12][4], M[6][4];
      float T[24];
      auto rows = [&]() {
#pragma unroll
        for (int k = 0; k < 12; ++k) yo[k] = pack_bf16(Z0[4 * (k % 6) + 2 * (k / 6)], Z0[4 * (k % 6) + 2 * (k / 6) + 1]);
#pragma unroll
        for (int n = 0; n < 4; ++n) store(yo, n, 1, op16, op8);
#pragma unroll
        for (int j = 0; j < 6; ++j) {
          sched_fence();
          float ev[4];
#pragma unroll
          for (int u = 0; u < 4; ++u) {
            const int i = 4 * j + u;
            ev[u] = fmah(fsub(Z1[i], Z2[i]), Z3[i]);
            Z0[i] = fmah(fadd(Z1[i], Z2[i]), Z0[i]);
          }
          ye[j] = pack_bf16(ev[0], ev[1]); ye[6 + j] = pack_bf16(ev[2], ev[3]);
          if (j == 3) { store(ye, 0, 1, op16 + orow, op8 + orow); store(ye, 1, 1, op16 + orow, op8 + orow); }
          if (j == 5) { store(ye, 2, 1, op16 + orow, op8 + orow); store(ye, 3, 1, op16 + orow, op8 + orow); }
        }
        sched_fence();
      };
      if (wg == 0) {
        rows();
        asm volatile("bar.sync 2, 288;" ::: "memory");
        asm volatile("bar.arrive 1, 288;" ::: "memory");
      } else {
        asm volatile("bar.sync 1, 288;" ::: "memory");
      }
#pragma unroll
      for (int cg = 0; cg < 12; ++cg) ldsm4(F[cg], la[cg] + wg * RING_BYTES + (NB & 1) * STAGE_BYTES);
      const uint64_t d0 = WDESC - dswap + zero2;
#pragma unroll
      for (int c = 0; c < 6; ++c) {
        M[c][0] = copy32(F[2 * c][1], zero2); M[c][1] = copy32(F[2 * c][2], zero2);
        M[c][2] = copy32(F[2 * c + 1][1], zero2); M[c][3] = copy32(F[2 * c + 1][2], zero2);
      }
      wg_fence();
#pragma unroll
      for (int c = 0; c < 6; ++c) {
        if (c == 0) mma48<0>(T, F[0], d0, d_outer(0, 0));
        else mma48<1>(T, F[2 * c], d0, d_outer(2 * c, 0));
        mma48<1>(T, F[2 * c + 1], d0, d_outer(2 * c + 1, 0));
        mma48<1>(T, M[c], d0, d_mid(c, 0));
      }
      wg_commit();
      if (wg == 1) rows();
      wg_wait<0>();
      pin(T);
#pragma unroll
      for (int k = 0; k < 12; ++k) {
        const int i = 4 * (k % 6) + 2 * (k / 6);
        yo[k] = pack_bf16(Z0[i] + T[i], Z0[i + 1] + T[i + 1]);
      }
#pragma unroll
      for (int n = 0; n < 4; ++n) store(yo, n, 1, op16 + 2 * orow, op8 + 2 * orow);
    }
  }
}

typedef CUresult (*EncodeTiledFn)(CUtensorMap*, CUtensorMapDataType, cuuint32_t, void*, const cuuint64_t*,
                                  const cuuint64_t*, const cuuint32_t*, const cuuint32_t*, CUtensorMapInterleave,
                                  CUtensorMapSwizzle, CUtensorMapL2promotion, CUtensorMapFloatOOBfill);

}

extern "C" void kernel_launch(void* const* d_in, const int* in_sizes, int n_in, void* d_out, int out_size) {
  (void)in_sizes; (void)n_in; (void)out_size;
  static EncodeTiledFn encode = nullptr;
  if (!encode) {
    void* fn = nullptr;
    cudaDriverEntryPointQueryResult qr;
    cudaGetDriverEntryPoint("cuTensorMapEncodeTiled", &fn, cudaEnableDefault, &qr);
    encode = (EncodeTiledFn)fn;
    cudaFuncSetAttribute(conv3x3_kernel, cudaFuncAttributeMaxDynamicSharedMemorySize, SMEM_BYTES);
  }
  CUtensorMap xmap;
  const cuuint64_t dims[3] = {64, (cuuint64_t)(OROW / 128), (cuuint64_t)IMG_H};
  const cuuint64_t strides[2] = {128, (cuuint64_t)OROW};
  const cuuint32_t box[3] = {64, ROW_LINES, 1};
  const cuuint32_t estr[3] = {1, 1, 1};
  encode(&xmap, CU_TENSOR_MAP_DATA_TYPE_BFLOAT16, 3, d_in[0], dims, strides, box, estr, CU_TENSOR_MAP_INTERLEAVE_NONE,
         CU_TENSOR_MAP_SWIZZLE_128B, CU_TENSOR_MAP_L2_PROMOTION_L2_256B, CU_TENSOR_MAP_FLOAT_OOB_FILL_NONE);
  conv3x3_kernel<<<128, NUM_THREADS, SMEM_BYTES, cudaStreamPerThread>>>(
      xmap, (const uint8_t*)d_in[0], (const uint8_t*)d_in[1], (const __nv_bfloat16*)d_in[2], (__nv_bfloat16*)d_out, 0u, 0u);
}
```

```cpp
#include <cuda_runtime.h>
#include <cuda_bf16.h>
#include <cuda.h>
#include <stdint.h>

#define DEVI __device__ __forceinline__

namespace {

constexpr int IMG_H = 512, IMG_W = 512, CH = 96;
constexpr int OROW = IMG_W * CH * 2;
constexpr int NB = 16;
constexpr int ROW_LINES = 100;
constexpr int ROW_TX = ROW_LINES * 128;
constexpr int ROW_PITCH = 13312;
constexpr int STAGE_BYTES = 2 * ROW_PITCH;
constexpr int RING_BYTES = 2 * STAGE_BYTES;
constexpr int W_TAP = 32 * CH * 2;
constexpr int W_RAW = 9 * W_TAP;
constexpr int W_OFF = RING_BYTES + W_RAW;
constexpr int W_SLOT = 32 * 48 * 2;
constexpr int W_KW = 4 * W_SLOT;
constexpr int W_3RD = 3 * W_KW;
constexpr int BAR_OFF = W_OFF + 3 * W_3RD;
constexpr int LA_OFF = BAR_OFF + 128;
constexpr int XCH_OFF = LA_OFF;
constexpr int SMEM_BYTES = XCH_OFF + 12288;
constexpr uint32_t SMEM_BASE = 1024;
constexpr int NUM_THREADS = 384;
constexpr int LDA = 3;
constexpr int GATE_R = 8;
constexpr int PF_START = 3, PF_DIST = 2;

constexpr uint64_t WDESC = (uint64_t)((SMEM_BASE + W_OFF) >> 4) | ((uint64_t)(128 >> 4) << 32);
__host__ __device__ constexpr int w_slot(int pos) { return pos == 0 ? 2 : pos == 1 ? 1 : pos == 2 ? 3 : 0; }
__host__ __device__ constexpr uint32_t d_outer(int cg, int pos) { return (uint32_t)((((cg >> 2) * W_3RD + w_slot(pos) * W_SLOT + (cg & 3) * 768) >> 4) | (((2 * W_KW) >> 4) << 16)); }
__host__ __device__ constexpr uint32_t d_mid(int c, int pos) { return (uint32_t)((((c >> 1) * W_3RD + W_KW + w_slot(pos) * W_SLOT + (c & 1) * 1536) >> 4) | ((768 >> 4) << 16)); }

DEVI uint32_t smem_u32(const void* p) { return (uint32_t)__cvta_generic_to_shared(p); }
DEVI void wg_fence() { asm volatile("wgmma.fence.sync.aligned;" ::: "memory"); }
DEVI void wg_commit() { asm volatile("wgmma.commit_group.sync.aligned;" ::: "memory"); }
template <int N> DEVI void wg_wait() { asm volatile("wgmma.wait_group.sync.aligned %0;" ::"n"(N) : "memory"); }
DEVI void proxy_fence() { asm volatile("fence.proxy.async.shared::cta;" ::: "memory"); }
DEVI void sched_fence() { asm volatile("pmevent 0;" ::: "memory"); }

DEVI void ldsm4(uint32_t (&r)[4], uint32_t addr) {
  asm volatile("ldmatrix.sync.aligned.m8n8.x4.shared.b16 {%0,%1,%2,%3}, [%4];"
               : "=r"(r[0]), "=r"(r[1]), "=r"(r[2]), "=r"(r[3]) : "r"(addr) : "memory");
}
DEVI void stsm4(uint32_t addr, uint32_t r0, uint32_t r1, uint32_t r2, uint32_t r3) {
  asm volatile("stmatrix.sync.aligned.m8n8.x4.shared.b16 [%0], {%1,%2,%3,%4};"
               ::"r"(addr), "r"(r0), "r"(r1), "r"(r2), "r"(r3) : "memory");
}
DEVI uint32_t hadd2(uint32_t a, uint32_t b) { uint32_t r; asm volatile("add.rn.bf16x2 %0, %1, %2;" : "=r"(r) : "r"(a), "r"(b)); return r; }
DEVI uint32_t hsub2(uint32_t a, uint32_t b) { uint32_t r; asm volatile("sub.rn.bf16x2 %0, %1, %2;" : "=r"(r) : "r"(a), "r"(b)); return r; }
DEVI uint32_t copy32(uint32_t a, uint32_t z) { uint32_t r; asm volatile("or.b32 %0, %1, %2;" : "=r"(r) : "r"(a), "r"(z)); return r; }
DEVI uint32_t pack_bf16(float lo, float hi) { uint32_t r; asm("cvt.rn.bf16x2.f32 %0, %1, %2;" : "=r"(r) : "f"(hi), "f"(lo)); return r; }
DEVI float fadd(float a, float b) { float r; asm volatile("add.rn.f32 %0, %1, %2;" : "=f"(r) : "f"(a), "f"(b)); return r; }
DEVI float fsub(float a, float b) { float r; asm volatile("sub.rn.f32 %0, %1, %2;" : "=f"(r) : "f"(a), "f"(b)); return r; }
DEVI float fmah(float a, float b) { float r; asm volatile("fma.rn.f32 %0, %1, 0f3F000000, %2;" : "=f"(r) : "f"(a), "f"(-b)); return r; }
DEVI float bf_lo(uint32_t v) { return __uint_as_float(v << 16); }
DEVI float bf_hi(uint32_t v) { return __uint_as_float(v & 0xffff0000u); }

DEVI void mbar_init(uint32_t bar, uint32_t cnt) { asm volatile("mbarrier.init.shared::cta.b64 [%0], %1;" ::"r"(bar), "r"(cnt) : "memory"); }
DEVI void mbar_expect_tx(uint32_t bar, uint32_t tx) { asm volatile("mbarrier.arrive.expect_tx.shared::cta.b64 _, [%0], %1;" ::"r"(bar), "r"(tx) : "memory"); }
DEVI void mbar_wait(uint32_t bar, uint32_t parity) {
  asm volatile(
      "{\n.reg .pred p;\n.reg .u32 c;\n"
      "mbarrier.try_wait.parity.shared::cta.b64 p, [%0], %1;\n"
      "@p bra.uni DONE;\n"
      "mov.u32 c, 0;\n"
      "SPIN:\n"
      "mbarrier.try_wait.parity.shared::cta.b64 p, [%0], %1, 100000;\n"
      "@p bra.uni DONE;\n"
      "add.u32 c, c, 1;\n"
      "setp.lt.u32 p, c, 0x4000;\n"
      "@p bra.uni SPIN;\n"
      "DONE:\n}\n" ::"r"(bar), "r"(parity) : "memory");
}
DEVI bool elect_one() {
  uint32_t p;
  asm volatile("{\n.reg .pred p;\nelect.sync _|p, 0xffffffff;\nselp.b32 %0, 1, 0, p;\n}\n" : "=r"(p));
  return p != 0;
}
DEVI void tma_row(uint32_t dst, const CUtensorMap* map, int line, int y, uint32_t bar) {
  asm volatile("cp.async.bulk.tensor.3d.shared::cluster.global.mbarrier::complete_tx::bytes [%0], [%1, {%3, %4, %5}], [%2];"
               ::"r"(dst), "l"(map), "r"(bar), "r"(0), "r"(line), "r"(y) : "memory");
}
DEVI void tma_row_both(uint32_t dst, const CUtensorMap* map, int line, int y, uint32_t bar) {
  asm volatile("cp.async.bulk.tensor.3d.shared::cluster.global.mbarrier::complete_tx::bytes.multicast::cluster [%0], [%1, {%3, %4, %5}], [%2], %6;"
               ::"r"(dst), "l"(map), "r"(bar), "r"(0), "r"(line), "r"(y), "h"((uint16_t)3) : "memory");
}
DEVI void tma_row_prefetch(const CUtensorMap* map, int line, int y) {
  asm volatile("cp.async.bulk.prefetch.tensor.3d.L2.global [%0, {%1, %2, %3}];" ::"l"(map), "r"(0), "r"(line), "r"(y) : "memory");
}

template <int ACC>
DEVI void mma48(float (&d)[24], const uint32_t (&a)[4], uint64_t dbase, uint32_t doff) {
  const uint64_t desc = dbase + (uint64_t)doff;
  asm volatile(
      "wgmma.mma_async.sync.aligned.m64n48k16.f32.bf16.bf16 "
      "{%0,%1,%2,%3,%4,%5,%6,%7,%8,%9,%10,%11,%12,%13,%14,%15,%16,%17,%18,%19,%20,%21,%22,%23}, "
      "{%24,%25,%26,%27}, %28, %29, 1, 1, 1;\n"
      : "+f"(d[0]), "+f"(d[1]), "+f"(d[2]), "+f"(d[3]), "+f"(d[4]), "+f"(d[5]), "+f"(d[6]), "+f"(d[7]),
        "+f"(d[8]), "+f"(d[9]), "+f"(d[10]), "+f"(d[11]), "+f"(d[12]), "+f"(d[13]), "+f"(d[14]), "+f"(d[15]),
        "+f"(d[16]), "+f"(d[17]), "+f"(d[18]), "+f"(d[19]), "+f"(d[20]), "+f"(d[21]), "+f"(d[22]), "+f"(d[23])
      : "r"(a[0]), "r"(a[1]), "r"(a[2]), "r"(a[3]), "l"(desc), "n"(ACC));
}
DEVI void pin(float (&d)[24]) {
#pragma unroll
  for (int i = 0; i < 24; ++i) asm volatile("" : "+f"(d[i]) :: "memory");
}

template <int OFF>
DEVI void st128(uint64_t p, int on, uint32_t a, uint32_t b, uint32_t c, uint32_t d) {
  asm volatile("{\n.reg .pred p;\nsetp.gt.s32 p, %5, 0;\n@p st.global.v4.b32 [%0+%6], {%1,%2,%3,%4};\n}\n"
               ::"l"(p), "r"(a), "r"(b), "r"(c), "r"(d), "r"(on), "n"(OFF) : "memory");
}
template <int OFF>
DEVI void st64(uint64_t p, int on, uint32_t a, uint32_t b) {
  asm volatile("{\n.reg .pred p;\nsetp.gt.s32 p, %3, 0;\n@p st.global.v2.b32 [%0+%4], {%1,%2};\n}\n"
               ::"l"(p), "r"(a), "r"(b), "r"(on), "n"(OFF) : "memory");
}

__global__ void __cluster_dims__(2, 1, 1) __launch_bounds__(NUM_THREADS, 1)
conv3x3_kernel(const __grid_constant__ CUtensorMap xmap, const __grid_constant__ CUtensorMap wmap,
               const uint8_t* __restrict__ xin, const uint8_t* __restrict__ wgt,
               const __nv_bfloat16* __restrict__ bias, __nv_bfloat16* __restrict__ out, uint32_t zero, uint32_t zero2) {
  extern __shared__ __align__(1024) uint8_t smem_raw[];
  if (threadIdx.x < 11) asm volatile("prefetch.global.L2 [%0];" ::"l"(wgt + min((blockIdx.x * 11 + threadIdx.x) * 128, 3 * W_RAW - 128)));
  const uint32_t sbase = smem_u32(smem_raw);
  const uint32_t bars = sbase + BAR_OFF;
  const int tid = threadIdx.x, warp = __shfl_sync(0xffffffffu, tid >> 5, 0), lane = tid & 31;
  const int half = blockIdx.x & 1, pair = blockIdx.x >> 1;
  const int off64 = half * 128, off32 = 64 + half * 32;
  const int line0 = (pair & 7) * 96 - 2, mid = (pair >> 3) * (4 * NB) + 2 * NB;

  auto xpf = [&](int k) {
    const int line = line0 + tid - 128 * k;
    if (tid >= 128 * k && tid < 128 * k + 100 && line >= 0 && line < OROW / 128)
      asm volatile("prefetch.global.L2 [%0];" ::"l"(xin + (size_t)(mid - 2 * k + half) * OROW + line * 128));
  };
  if (warp == 11) {
    if (elect_one()) {
#pragma unroll
      for (int i = 0; i < 11; ++i) mbar_init(bars + 8 * i, 1);
      asm volatile("fence.mbarrier_init.release.cluster;" ::: "memory");
      proxy_fence();
#pragma unroll
      for (int i = 0; i < 3; ++i) {
        if (i == 2) {
          mbar_expect_tx(bars, 2 * ROW_TX);
          tma_row(sbase, &xmap, line0, mid, bars);
          tma_row(sbase + ROW_PITCH, &xmap, line0, mid + 1, bars);
        }
        mbar_expect_tx(bars + 64 + 8 * i, W_RAW);
        tma_row(sbase + RING_BYTES + ((i + 1) % 3) * W_RAW, &wmap, 48 * i, 0, bars + 64 + 8 * i);
      }
    }
  }
  if ((sbase & 0xFFFFFFu) != SMEM_BASE) __trap();
  const uint4 bias_v = __ldg(reinterpret_cast<const uint4*>(bias + off64 / 2 + 8 * (lane & 3)));
  const uint2 bias_u = __ldg(reinterpret_cast<const uint2*>(bias + off32 / 2 + 4 * (lane & 3)));
  if (warp < 4) __nanosleep(150);
  xpf(0);
  float Z0[24], Z1[24], Z2[24], Z3[24];
  if (warp < 8) {
    const uint32_t r[6] = {bias_v.x, bias_v.y, bias_v.z, bias_v.w, bias_u.x, bias_u.y};
#pragma unroll
    for (int i = 0; i < 24; ++i) {
      const float b = (i & 1) ? bf_hi(r[i >> 2]) : bf_lo(r[i >> 2]), z = __uint_as_float(zero);
      Z0[i] = fadd(z, z); Z1[i] = fadd(b, b); Z2[i] = fadd(z, z); Z3[i] = fadd(z, z);
    }
  }
  __syncthreads();
  xpf(1);
  asm volatile("barrier.cluster.arrive.relaxed.aligned;" ::: "memory");
  {
    const int p = 16 * (warp & 3) + 2 * (lane & 7) - 1 + (lane >> 3);
    const uint32_t off = 192 * p + 256 + 64 * (warp >> 2), a0 = sbase + (off ^ (((off >> 7) & 7) << 4));
    asm volatile("st.shared.v4.b32 [%0], {%1,%2,%3,%4};" ::"r"(sbase + LA_OFF + tid * 16), "r"(a0), "r"(a0 ^ 16), "r"(a0 ^ 32), "r"(a0 ^ 48) : "memory");
  }
  auto w_fetch = [&](uint32_t (&raw)[3][6], uint32_t src) {
#pragma unroll
    for (int kh = 0; kh < 3; ++kh) {
      asm volatile("ld.shared.v4.b32 {%0,%1,%2,%3}, [%4];" : "=r"(raw[kh][0]), "=r"(raw[kh][1]), "=r"(raw[kh][2]), "=r"(raw[kh][3])
                   : "r"(src + kh * 3 * W_TAP + off64 + 16 * (lane & 3)) : "memory");
      asm volatile("ld.shared.v2.b32 {%0,%1}, [%2];" : "=r"(raw[kh][4]), "=r"(raw[kh][5])
                   : "r"(src + kh * 3 * W_TAP + off32 + 8 * (lane & 3)) : "memory");
    }
  };
  auto w_store = [&](const uint32_t (&raw)[3][6], uint32_t blk) {
    const uint32_t d4 = blk + lane * 16;
    const uint32_t d2 = blk + 512 + (lane & 15) * 16 + (lane >> 4) * (2 * W_SLOT);
    stsm4(d4, raw[0][0], raw[0][1], raw[0][2], raw[0][3]);
    stsm4(d4 + 2 * W_SLOT, raw[2][0], raw[2][1], raw[2][2], raw[2][3]);
    stsm4(d2, raw[0][4], raw[0][5], raw[2][4], raw[2][5]);
    uint32_t u1[6], u2[6];
#pragma unroll
    for (int j = 0; j < 6; ++j) {
      auto lo = [&](uint32_t v) { return __uint_as_float(v * (65536u + zero)); };
      const float tl = lo(raw[0][j]) + lo(raw[2][j]), th = bf_hi(raw[0][j]) + bf_hi(raw[2][j]);
      const float ml = lo(raw[1][j]), mh = bf_hi(raw[1][j]);
      u1[j] = pack_bf16(tl + ml, th + mh);
      u2[j] = pack_bf16(tl - ml, th - mh);
    }
    stsm4(d4 + W_SLOT, u1[0], u1[1], u1[2], u1[3]);
    stsm4(d4 + 3 * W_SLOT, u2[0], u2[1], u2[2], u2[3]);
    stsm4(d2 + W_SLOT, u1[4], u1[5], u2[4], u2[5]);
  };
  const uint32_t w_src = sbase + RING_BYTES + ((warp & 3) * 8 + (lane >> 2)) * 192, w_dst = sbase + W_OFF + (warp & 3) * 768;
#pragma unroll 1
  for (int i = 0; i < 2; ++i) {
    uint32_t raw[3][6];
    mbar_wait(bars + 64 + 8 * i, 0);
    w_fetch(raw, w_src + (i + 1) * W_RAW + (warp >> 2) * W_TAP);
    __syncthreads();
    w_store(raw, w_dst + i * W_3RD + (warp >> 2) * W_KW);
  }
  proxy_fence();
  asm volatile("barrier.cluster.wait.aligned;" ::: "memory");
  __syncthreads();

  if (warp >= 8) {
    asm volatile("setmaxnreg.dec.sync.aligned.u32 56;");
    if (warp < 10) {
      const int w = warp - 8, o = w ^ 1, dir = 1 - 2 * o;
      const int ybase = mid - o;
      uint32_t peer_free;
      asm volatile("mapa.shared::cluster.u32 %0, %1, %2;" : "=r"(peer_free) : "r"(bars + 32 + 16 * w), "r"(half ^ 1));
      auto first = [&]() {
        if (elect_one()) {
          const uint32_t dst = sbase + o * RING_BYTES + w * STAGE_BYTES, fb = bars + o * 16 + w * 8;
          mbar_expect_tx(fb, 2 * ROW_TX);
          tma_row(dst, &xmap, line0, ybase + dir * 2 * w, fb);
          tma_row(dst + ROW_PITCH, &xmap, line0, ybase + dir * (2 * w + 1), fb);
        }
      };
      if (w == 1) first();
#pragma unroll 1
      for (int t = 0; t <= NB; ++t) {
        mbar_wait(bars + w * 16 + (t & 1) * 8, (t >> 1) & 1);
        if (t * w == 1) asm volatile("bar.sync 4, 96;" ::: "memory");
        asm volatile("bar.sync %0, 288;" ::"r"(2 - w) : "memory");
        if (t + w == 0) first();
        const int tn = t + 1 + w;
        const uint32_t dst = sbase + o * RING_BYTES + (tn & 1) * STAGE_BYTES, fb = bars + o * 16 + (tn & 1) * 8;
        if (tn < NB) {
          if (elect_one()) {
            mbar_expect_tx(fb, 2 * ROW_TX);
            asm volatile("mbarrier.arrive.relaxed.cluster.shared::cluster.b64 _, [%0];" ::"r"(peer_free + (t & 1) * 8) : "memory");
          }
          mbar_wait(bars + 32 + 16 * w + (t & 1) * 8, (t >> 1) & 1);
          if (elect_one()) tma_row_both(dst + half * ROW_PITCH, &xmap, line0, ybase + dir * (2 * tn + half), fb);
        } else if (tn == NB && elect_one()) {
          mbar_expect_tx(fb, ROW_TX);
          tma_row(dst, &xmap, line0, ybase + dir * 2 * NB, fb);
        }
        if (tn >= PF_START && tn + PF_DIST < NB && elect_one()) tma_row_prefetch(&xmap, line0, ybase + dir * (2 * (tn + PF_DIST) + half));
      }
    } else {
      const int h = warp - 10;
      const uint32_t xch = sbase + XCH_OFF + lane * 16;
      uint32_t v[4][2][4];
      asm volatile("bar.sync 3, 192;" ::: "memory");
#pragma unroll
      for (int w = 0; w < 4; ++w) {
#pragma unroll
        for (int n = 0; n < 2; ++n) {
          asm volatile("ld.shared.v4.b32 {%0,%1,%2,%3}, [%4];" : "=r"(v[w][n][0]), "=r"(v[w][n][1]), "=r"(v[w][n][2]), "=r"(v[w][n][3])
                       : "r"(xch + (3 * h + n) * 2048 + w * 512) : "memory");
        }
      }
      asm volatile("bar.arrive 4, 96;" ::: "memory");
      asm volatile("bar.sync 3, 192;" ::: "memory");
      const uint64_t p16 = (uint64_t)__cvta_generic_to_global(out) + (size_t)(mid - h) * OROW + ((pair & 7) * 64 + 2 * (lane >> 2)) * (CH * 2) + off64 + 16 * (lane & 3);
      const uint64_t p8 = p16 + (int64_t)(off32 - off64 - 8 * (lane & 3));
#pragma unroll
      for (int w = 0; w < 4; ++w) {
#pragma unroll
        for (int n = 0; n < 3; ++n) {
          __nanosleep(400);
          uint32_t a, b, c, d, q[4];
          if (n < 2) {
            asm volatile("ld.shared.v4.b32 {%0,%1,%2,%3}, [%4];" : "=r"(a), "=r"(b), "=r"(c), "=r"(d) : "r"(xch + (3 * (1 - h) + n) * 2048 + w * 512) : "memory");
            q[0] = v[w][n & 1][0]; q[1] = v[w][n & 1][1]; q[2] = v[w][n & 1][2]; q[3] = v[w][n & 1][3];
          } else {
            asm volatile("ld.shared.v4.b32 {%0,%1,%2,%3}, [%4];" : "=r"(a), "=r"(b), "=r"(c), "=r"(d) : "r"(sbase + ROW_TX + (w + 4 * (1 - h)) * ROW_PITCH + lane * 16) : "memory");
            asm volatile("ld.shared.v4.b32 {%0,%1,%2,%3}, [%4];" : "=r"(q[0]), "=r"(q[1]), "=r"(q[2]), "=r"(q[3]) : "r"(xch + (3 * h + 2) * 2048 + w * 512) : "memory");
          }
          a = hadd2(a, q[0]); b = hadd2(b, q[1]); c = hadd2(c, q[2]); d = hadd2(d, q[3]);
          if (n == 0) st128<0>(p16 + w * 3072, 1, a, b, c, d);
          if (n == 1) st128<192>(p16 + w * 3072, 1, a, b, c, d);
          if (n == 2) { st64<0>(p8 + w * 3072, 1, a, b); st64<192>(p8 + w * 3072, 1, c, d); }
        }
      }
    }
  } else {
    asm volatile("setmaxnreg.inc.sync.aligned.u32 224;");
    const int wg = warp >> 2, w = warp & 3;
    const int g = lane >> 2, t4 = lane & 3;
    if (wg == 1) {
      uint32_t raw[3][3][6];
      mbar_wait(bars + 80, 0);
#pragma unroll
      for (int kw = 0; kw < 3; ++kw) w_fetch(raw[kw], w_src + kw * W_TAP);
      asm volatile("bar.arrive 2, 288;" ::: "memory");
#pragma unroll
      for (int kw = 0; kw < 3; ++kw) w_store(raw[kw], w_dst + 2 * W_3RD + kw * W_KW);
      proxy_fence();
      asm volatile("bar.arrive 5, 256;" ::: "memory");
    }

    uint32_t la[12];
#pragma unroll
    for (int q = 0; q < 3; ++q)
      asm volatile("ld.shared.v4.b32 {%0,%1,%2,%3}, [%4];" : "=r"(la[4 * q]), "=r"(la[4 * q + 1]), "=r"(la[4 * q + 2]), "=r"(la[4 * q + 3])
                   : "r"(sbase + LA_OFF + q * 2048 + (tid & 127) * 16) : "memory");
    uint32_t soff = wg * RING_BYTES;
    float b2[12];
    {
      const uint32_t r[6] = {bias_v.x, bias_v.y, bias_v.z, bias_v.w, bias_u.x, bias_u.y};
#pragma unroll
      for (int j = 0; j < 6; ++j) { b2[2 * j] = 2.f * bf_lo(r[j]); b2[2 * j + 1] = 2.f * bf_hi(r[j]); }
    }
    const int orow = wg ? -OROW : OROW;
    uint64_t op16 = (uint64_t)__cvta_generic_to_global(out) + (ptrdiff_t)(mid - wg) * OROW - (ptrdiff_t)orow
                    + ((pair & 7) * 64 + 16 * w + 2 * g) * (CH * 2) + off64 + 16 * t4;
    uint64_t op8 = op16 + (int64_t)(off32 - off64 - 8 * t4);
    op16 -= 2 * (int64_t)orow; op8 -= 2 * (int64_t)orow;
    uint64_t oq16 = op16 + orow, oq8 = op8 + orow;
    const int64_t ostep = 2 * (int64_t)orow;
    auto advance = [&](uint64_t& p) { asm volatile("add.s64 %0, %0, %1;" : "+l"(p) : "l"(ostep)); };
    const uint64_t dswap = wg ? (uint64_t)((2 * W_SLOT) >> 4) : 0;

    constexpr int NAB = LDA + 2;
    uint32_t A[NAB][4], B[NAB][4], S[3][4], D[3][4], MP[3][4], MQ[3][4];
    auto store = [&](const uint32_t (&y)[12], int n, int on, uint64_t p16, uint64_t p8) {
      if (n == 0) st128<0>(p16, on, y[0], y[1], y[2], y[3]);
      if (n == 1) st128<192>(p16, on, y[6], y[7], y[8], y[9]);
      if (n == 2) st64<0>(p8, on, y[4], y[5]);
      if (n == 3) st64<192>(p8, on, y[10], y[11]);
    };
    auto load = [&](int cg) { ldsm4(A[cg % NAB], la[cg] + soff); ldsm4(B[cg % NAB], la[cg] + soff + ROW_PITCH); };
    const uint32_t vzero = __shfl_sync(0xffffffffu, (uint32_t)tid & zero2, lane);
    uint32_t clk = 0;
    auto prep = [&](int r) {
#pragma unroll
      for (int i = 0; i < 4; ++i) {
        const int src = ((r - 1) & ~1) + (i >> 1), k = 1 + (i & 1);
        if (r < 12) S[r % 3][i] = hadd2(A[r % NAB][i], B[r % NAB][i]);
        if (r > 0) MP[r % 3][i] = copy32((r & 1) ? A[src % NAB][k] : S[src % 3][k], zero2);
        if (r < 12) D[r % 3][i] = hsub2(A[r % NAB][i], B[r % NAB][i]);
        if (r > 0) {
          const uint32_t v = (r & 1) ? B[src % NAB][k] : D[src % 3][k];
          if (i == 3 && r >= 2) asm volatile("lop3.b32 %0, %1, %2, %3, 0xF8;" : "=r"(MQ[r % 3][i]) : "r"(v), "r"(clk), "r"(vzero));
          else MQ[r % 3][i] = copy32(v, zero2);
        }
      }
    };

#pragma unroll
    for (int i = 0; i < 4; ++i) { A[11 % NAB][i] = 0; B[11 % NAB][i] = 0; S[11 % 3][i] = 0; D[11 % 3][i] = 0; MP[12 % 3][i] = 0; MQ[12 % 3][i] = 0; }

    for (int t = 0; t < NB; ++t) {
      uint32_t yo[12], ye[12];
#pragma unroll
      for (int i = 0; i < 4; ++i) {
        yo[i] = A[11 % NAB][i]; yo[6 + i] = B[11 % NAB][i]; ye[i] = S[11 % 3][i]; ye[6 + i] = D[11 % 3][i];
        yo[4 + (i & 1) + 6 * (i >> 1)] = MP[12 % 3][i]; ye[4 + (i & 1) + 6 * (i >> 1)] = MQ[12 % 3][i];
      }
      auto block = [&](int k) {
        if (t > (int)((k & 1) ? zero : zero2)) {
          float ev[2];
#pragma unroll
          for (int u = 0; u < 2; ++u) {
            const int e = k / 6, j = k % 6, i = 4 * j + 2 * e + u;
            if (u == 0) yo[k] = pack_bf16(Z0[i], Z0[i + 1]);
            const float sm = Z1[i] + Z2[i], df = Z1[i] - Z2[i];
            const float p = fmaf(0.5f, sm, -Z0[i]);
            ev[u] = fmaf(0.5f, df, -Z3[i]);
            Z0[i] = p;
            Z1[i] = (p + b2[2 * j + u]) + Z3[i];
            Z2[i] = p - Z3[i];
            if (u == 1) ye[k] = pack_bf16(ev[0], ev[1]);
            if (j == 3 && u == 0) store(yo, e, t - 1, op16, op8);
            if (j == 4 && u == 0) store(ye, e, t - 1, oq16, oq8);
            if (j == 5 && u == 0) store(yo, 2 + e, t - 1, op16, op8);
            if (j == 5 && u == 1) store(ye, 2 + e, t - 1, oq16, oq8);
            if (k == 0 && u == 0) { advance(op16); advance(op8); }
            if (k == 1 && u == 0) { advance(oq16); advance(oq8); }
          }
        }
      };
      if (t > 0) {
#pragma unroll
        for (int k = 0; k < 10; ++k) block(k);
      }
      soff = wg * RING_BYTES + (t & 1) * STAGE_BYTES;
      if (wg) asm volatile("bar.sync 1, 288;" ::: "memory"); else asm volatile("bar.sync 2, 288;" ::: "memory");
      load(0);
      block(10);
      load(1);
      block(11);
      if (t == 1) {
        const uint32_t xch = sbase + XCH_OFF + (tid & 127) * 16;
        auto put = [&](int n, uint32_t a, uint32_t b, uint32_t c, uint32_t d) {
          asm volatile("st.shared.v4.b32 [%0], {%1,%2,%3,%4};" ::"r"(xch + n * 2048), "r"(a), "r"(b), "r"(c), "r"(d) : "memory");
        };
        put(0, ye[0], ye[1], ye[2], ye[3]); put(1, ye[6], ye[7], ye[8], ye[9]);
        put(3, yo[0], yo[1], yo[2], yo[3]); put(4, yo[6], yo[7], yo[8], yo[9]);
        const uint32_t x2 = wg ? sbase + ROW_TX + w * ROW_PITCH + lane * 16 : xch + 2 * 2048, x5 = x2 + (wg ? 4 * ROW_PITCH : 3 * 2048);
        asm volatile("st.shared.v4.b32 [%0], {%1,%2,%3,%4};" ::"r"(x2), "r"(ye[4]), "r"(ye[5]), "r"(ye[10]), "r"(ye[11]) : "memory");
        asm volatile("st.shared.v4.b32 [%0], {%1,%2,%3,%4};" ::"r"(x5), "r"(yo[4]), "r"(yo[5]), "r"(yo[10]), "r"(yo[11]) : "memory");
        asm volatile("bar.arrive 3, 192;" ::: "memory");
      }
      load(2);
      prep(0);
      const uint64_t dbase = WDESC + (uint64_t)(t & zero), db0 = dbase - dswap, db3 = dbase + dswap;
      wg_fence();
#pragma unroll
      for (int r = 0; r < 13; ++r) {
        if (r < 12) {
          mma48<1>(Z0, A[r % NAB], db0, d_outer(r, 0));
          mma48<1>(Z1, S[r % 3], dbase, d_outer(r, 1));
          mma48<1>(Z2, D[r % 3], dbase, d_outer(r, 2));
          if (r == 0) mma48<0>(Z3, B[r % NAB], db3, d_outer(r, 3));
          else mma48<1>(Z3, B[r % NAB], db3, d_outer(r, 3));
        }
        if (r > 0) {
          const int c = (r - 1) >> 1;
          if (r & 1) { mma48<1>(Z0, MP[r % 3], db0, d_mid(c, 0)); mma48<1>(Z3, MQ[r % 3], db3, d_mid(c, 3)); }
          else       { mma48<1>(Z1, MP[r % 3], dbase, d_mid(c, 1)); mma48<1>(Z2, MQ[r % 3], dbase, d_mid(c, 2)); }
        }
        wg_commit();
        if (r + LDA < 12) load(r + LDA);
        static_assert(LDA == 3 && GATE_R + LDA >= 11, "the gate arrival doubles as the stage release");
        if (r == GATE_R) asm volatile("bar.arrive %0, 288;" ::"r"(1 + wg) : "memory");
        if (r < 12) {
          prep(r + 1);
          if (r == 7 && t + wg == 0) asm volatile("bar.sync 5, 256;" ::: "memory");
          wg_fence();
          wg_wait<1>();
          if (r < 11) asm volatile("mov.u32 %0, %clock;" : "=r"(clk) :: "memory");
        } else {
          wg_wait<0>();
        }
      }
      pin(Z0); pin(Z1); pin(Z2); pin(Z3);
    }
    advance(op16); advance(op8);

    {
      uint32_t yo[12], ye[12], F[12][4], M[6][4];
      float T[24];
      auto rows = [&]() {
#pragma unroll
        for (int k = 0; k < 12; ++k) yo[k] = pack_bf16(Z0[4 * (k % 6) + 2 * (k / 6)], Z0[4 * (k % 6) + 2 * (k / 6) + 1]);
#pragma unroll
        for (int n = 0; n < 4; ++n) store(yo, n, 1, op16, op8);
#pragma unroll
        for (int j = 0; j < 6; ++j) {
          sched_fence();
          float ev[4];
#pragma unroll
          for (int u = 0; u < 4; ++u) {
            const int i = 4 * j + u;
            ev[u] = fmah(fsub(Z1[i], Z2[i]), Z3[i]);
            Z0[i] = fmah(fadd(Z1[i], Z2[i]), Z0[i]);
          }
          ye[j] = pack_bf16(ev[0], ev[1]); ye[6 + j] = pack_bf16(ev[2], ev[3]);
          if (j == 3) { store(ye, 0, 1, op16 + orow, op8 + orow); store(ye, 1, 1, op16 + orow, op8 + orow); }
          if (j == 5) { store(ye, 2, 1, op16 + orow, op8 + orow); store(ye, 3, 1, op16 + orow, op8 + orow); }
        }
        sched_fence();
      };
      if (wg == 0) {
        rows();
        asm volatile("bar.sync 2, 288;" ::: "memory");
        asm volatile("bar.arrive 1, 288;" ::: "memory");
      } else {
        asm volatile("bar.sync 1, 288;" ::: "memory");
      }
#pragma unroll
      for (int cg = 0; cg < 12; ++cg) ldsm4(F[cg], la[cg] + wg * RING_BYTES + (NB & 1) * STAGE_BYTES);
      const uint64_t d0 = WDESC - dswap + zero2;
#pragma unroll
      for (int c = 0; c < 6; ++c) {
        M[c][0] = copy32(F[2 * c][1], zero2); M[c][1] = copy32(F[2 * c][2], zero2);
        M[c][2] = copy32(F[2 * c + 1][1], zero2); M[c][3] = copy32(F[2 * c + 1][2], zero2);
      }
      wg_fence();
#pragma unroll
      for (int c = 0; c < 6; ++c) {
        if (c == 0) mma48<0>(T, F[0], d0, d_outer(0, 0));
        else mma48<1>(T, F[2 * c], d0, d_outer(2 * c, 0));
        mma48<1>(T, F[2 * c + 1], d0, d_outer(2 * c + 1, 0));
        mma48<1>(T, M[c], d0, d_mid(c, 0));
      }
      wg_commit();
      if (wg == 1) rows();
      wg_wait<0>();
      pin(T);
#pragma unroll
      for (int k = 0; k < 12; ++k) {
        const int i = 4 * (k % 6) + 2 * (k / 6);
        yo[k] = pack_bf16(Z0[i] + T[i], Z0[i + 1] + T[i + 1]);
      }
#pragma unroll
      for (int n = 0; n < 4; ++n) store(yo, n, 1, op16 + 2 * orow, op8 + 2 * orow);
    }
  }
}

typedef CUresult (*EncodeTiledFn)(CUtensorMap*, CUtensorMapDataType, cuuint32_t, void*, const cuuint64_t*,
                                  const cuuint64_t*, const cuuint32_t*, const cuuint32_t*, CUtensorMapInterleave,
                                  CUtensorMapSwizzle, CUtensorMapL2promotion, CUtensorMapFloatOOBfill);

}

extern "C" void kernel_launch(void* const* d_in, const int* in_sizes, int n_in, void* d_out, int out_size) {
  (void)in_sizes; (void)n_in; (void)out_size;
  static EncodeTiledFn encode = nullptr;
  if (!encode) {
    void* fn = nullptr;
    cudaDriverEntryPointQueryResult qr;
    cudaGetDriverEntryPoint("cuTensorMapEncodeTiled", &fn, cudaEnableDefault, &qr);
    encode = (EncodeTiledFn)fn;
    cudaFuncSetAttribute(conv3x3_kernel, cudaFuncAttributeMaxDynamicSharedMemorySize, SMEM_BYTES);
  }
  CUtensorMap xmap;
  const cuuint64_t dims[3] = {64, (cuuint64_t)(OROW / 128), (cuuint64_t)IMG_H};
  const cuuint64_t strides[2] = {128, (cuuint64_t)OROW};
  const cuuint32_t box[3] = {64, ROW_LINES, 1};
  const cuuint32_t estr[3] = {1, 1, 1};
  encode(&xmap, CU_TENSOR_MAP_DATA_TYPE_BFLOAT16, 3, d_in[0], dims, strides, box, estr, CU_TENSOR_MAP_INTERLEAVE_NONE,
         CU_TENSOR_MAP_SWIZZLE_128B, CU_TENSOR_MAP_L2_PROMOTION_L2_256B, CU_TENSOR_MAP_FLOAT_OOB_FILL_NONE);
  CUtensorMap wmap;
  const cuuint64_t wdims[3] = {64, CH * CH * 2 / 128, 9};
  const cuuint64_t wstrides[2] = {128, CH * CH * 2};
  const cuuint32_t wbox[3] = {64, W_TAP / 128, 9};
  encode(&wmap, CU_TENSOR_MAP_DATA_TYPE_BFLOAT16, 3, d_in[1], wdims, wstrides, wbox, estr, CU_TENSOR_MAP_INTERLEAVE_NONE,
         CU_TENSOR_MAP_SWIZZLE_NONE, CU_TENSOR_MAP_L2_PROMOTION_L2_256B, CU_TENSOR_MAP_FLOAT_OOB_FILL_NONE);
  conv3x3_kernel<<<128, NUM_THREADS, SMEM_BYTES, cudaStreamPerThread>>>(
      xmap, wmap, (const uint8_t*)d_in[0], (const uint8_t*)d_in[1], (const __nv_bfloat16*)d_in[2], (__nv_bfloat16*)d_out, 0u, 0u);
}
```

```cpp
#include <cuda_runtime.h>
#include <cuda_bf16.h>
#include <cuda.h>
#include <stdint.h>

#define DEVI __device__ __forceinline__

namespace {

constexpr int IMG_H = 512, IMG_W = 512, CH = 96;
constexpr int OROW = IMG_W * CH * 2;
constexpr int NB = 16;
constexpr int ROW_LINES = 100;
constexpr int ROW_TX = ROW_LINES * 128;
constexpr int ROW_PITCH = 13312;
constexpr int STAGE_BYTES = 2 * ROW_PITCH;
constexpr int RING_BYTES = 2 * STAGE_BYTES;
constexpr int W_TAP = 32 * CH * 2;
constexpr int W_RAW = 9 * W_TAP;
constexpr int W_OFF = RING_BYTES + W_RAW;
constexpr int W_SLOT = 32 * 48 * 2;
constexpr int W_KW = 4 * W_SLOT;
constexpr int W_3RD = 3 * W_KW;
constexpr int BAR_OFF = W_OFF + 3 * W_3RD;
constexpr int LA_OFF = BAR_OFF + 128;
constexpr int XCH_OFF = LA_OFF;
constexpr int SMEM_BYTES = XCH_OFF + 12288;
constexpr uint32_t SMEM_BASE = 1024;
constexpr int NUM_THREADS = 384;
constexpr int LDA = 3;
constexpr int GATE_R = 8;
constexpr int PF_START = 3, PF_DIST = 2;

constexpr uint64_t WDESC = (uint64_t)((SMEM_BASE + W_OFF) >> 4) | ((uint64_t)(128 >> 4) << 32);
__host__ __device__ constexpr int w_slot(int pos) { return pos == 0 ? 2 : pos == 1 ? 1 : pos == 2 ? 3 : 0; }
__host__ __device__ constexpr uint32_t d_outer(int cg, int pos) { return (uint32_t)((((cg >> 2) * W_3RD + w_slot(pos) * W_SLOT + (cg & 3) * 768) >> 4) | (((2 * W_KW) >> 4) << 16)); }
__host__ __device__ constexpr uint32_t d_mid(int c, int pos) { return (uint32_t)((((c >> 1) * W_3RD + W_KW + w_slot(pos) * W_SLOT + (c & 1) * 1536) >> 4) | ((768 >> 4) << 16)); }

DEVI uint32_t smem_u32(const void* p) { return (uint32_t)__cvta_generic_to_shared(p); }
DEVI void wg_fence() { asm volatile("wgmma.fence.sync.aligned;" ::: "memory"); }
DEVI void wg_commit() { asm volatile("wgmma.commit_group.sync.aligned;" ::: "memory"); }
template <int N> DEVI void wg_wait() { asm volatile("wgmma.wait_group.sync.aligned %0;" ::"n"(N) : "memory"); }
DEVI void proxy_fence() { asm volatile("fence.proxy.async.shared::cta;" ::: "memory"); }
DEVI void sched_fence() { asm volatile("pmevent 0;" ::: "memory"); }

DEVI void ldsm4(uint32_t (&r)[4], uint32_t addr) {
  asm volatile("ldmatrix.sync.aligned.m8n8.x4.shared.b16 {%0,%1,%2,%3}, [%4];"
               : "=r"(r[0]), "=r"(r[1]), "=r"(r[2]), "=r"(r[3]) : "r"(addr) : "memory");
}
DEVI void stsm4(uint32_t addr, uint32_t r0, uint32_t r1, uint32_t r2, uint32_t r3) {
  asm volatile("stmatrix.sync.aligned.m8n8.x4.shared.b16 [%0], {%1,%2,%3,%4};"
               ::"r"(addr), "r"(r0), "r"(r1), "r"(r2), "r"(r3) : "memory");
}
DEVI uint32_t hadd2(uint32_t a, uint32_t b) { uint32_t r; asm volatile("add.rn.bf16x2 %0, %1, %2;" : "=r"(r) : "r"(a), "r"(b)); return r; }
DEVI uint32_t hsub2(uint32_t a, uint32_t b) { uint32_t r; asm volatile("sub.rn.bf16x2 %0, %1, %2;" : "=r"(r) : "r"(a), "r"(b)); return r; }
DEVI uint32_t copy32(uint32_t a, uint32_t z) { uint32_t r; asm volatile("or.b32 %0, %1, %2;" : "=r"(r) : "r"(a), "r"(z)); return r; }
DEVI uint32_t pack_bf16(float lo, float hi) { uint32_t r; asm("cvt.rn.bf16x2.f32 %0, %1, %2;" : "=r"(r) : "f"(hi), "f"(lo)); return r; }
DEVI float fadd(float a, float b) { float r; asm volatile("add.rn.f32 %0, %1, %2;" : "=f"(r) : "f"(a), "f"(b)); return r; }
DEVI float fsub(float a, float b) { float r; asm volatile("sub.rn.f32 %0, %1, %2;" : "=f"(r) : "f"(a), "f"(b)); return r; }
DEVI float fmah(float a, float b) { float r; asm volatile("fma.rn.f32 %0, %1, 0f3F000000, %2;" : "=f"(r) : "f"(a), "f"(-b)); return r; }
DEVI float bf_lo(uint32_t v) { return __uint_as_float(v << 16); }
DEVI float bf_hi(uint32_t v) { return __uint_as_float(v & 0xffff0000u); }

DEVI void mbar_init(uint32_t bar, uint32_t cnt) { asm volatile("mbarrier.init.shared::cta.b64 [%0], %1;" ::"r"(bar), "r"(cnt) : "memory"); }
DEVI void mbar_expect_tx(uint32_t bar, uint32_t tx) { asm volatile("mbarrier.arrive.expect_tx.shared::cta.b64 _, [%0], %1;" ::"r"(bar), "r"(tx) : "memory"); }
DEVI void mbar_wait(uint32_t bar, uint32_t parity) {
  asm volatile(
      "{\n.reg .pred p;\n.reg .u32 c;\n"
      "mbarrier.try_wait.parity.shared::cta.b64 p, [%0], %1;\n"
      "@p bra.uni DONE;\n"
      "mov.u32 c, 0;\n"
      "SPIN:\n"
      "mbarrier.try_wait.parity.shared::cta.b64 p, [%0], %1, 100000;\n"
      "@p bra.uni DONE;\n"
      "add.u32 c, c, 1;\n"
      "setp.lt.u32 p, c, 0x4000;\n"
      "@p bra.uni SPIN;\n"
      "DONE:\n}\n" ::"r"(bar), "r"(parity) : "memory");
}
DEVI bool elect_one() {
  uint32_t p;
  asm volatile("{\n.reg .pred p;\nelect.sync _|p, 0xffffffff;\nselp.b32 %0, 1, 0, p;\n}\n" : "=r"(p));
  return p != 0;
}
DEVI void tma_row(uint32_t dst, const CUtensorMap* map, int line, int y, uint32_t bar) {
  asm volatile("cp.async.bulk.tensor.3d.shared::cluster.global.mbarrier::complete_tx::bytes [%0], [%1, {%3, %4, %5}], [%2];"
               ::"r"(dst), "l"(map), "r"(bar), "r"(0), "r"(line), "r"(y) : "memory");
}
DEVI void tma_row_both(uint32_t dst, const CUtensorMap* map, int line, int y, uint32_t bar) {
  asm volatile("cp.async.bulk.tensor.3d.shared::cluster.global.mbarrier::complete_tx::bytes.multicast::cluster [%0], [%1, {%3, %4, %5}], [%2], %6;"
               ::"r"(dst), "l"(map), "r"(bar), "r"(0), "r"(line), "r"(y), "h"((uint16_t)3) : "memory");
}
DEVI void tma_row_prefetch(const CUtensorMap* map, int line, int y) {
  asm volatile("cp.async.bulk.prefetch.tensor.3d.L2.global [%0, {%1, %2, %3}];" ::"l"(map), "r"(0), "r"(line), "r"(y) : "memory");
}

template <int ACC>
DEVI void mma48(float (&d)[24], const uint32_t (&a)[4], uint64_t dbase, uint32_t doff) {
  const uint64_t desc = dbase + (uint64_t)doff;
  asm volatile(
      "wgmma.mma_async.sync.aligned.m64n48k16.f32.bf16.bf16 "
      "{%0,%1,%2,%3,%4,%5,%6,%7,%8,%9,%10,%11,%12,%13,%14,%15,%16,%17,%18,%19,%20,%21,%22,%23}, "
      "{%24,%25,%26,%27}, %28, %29, 1, 1, 1;\n"
      : "+f"(d[0]), "+f"(d[1]), "+f"(d[2]), "+f"(d[3]), "+f"(d[4]), "+f"(d[5]), "+f"(d[6]), "+f"(d[7]),
        "+f"(d[8]), "+f"(d[9]), "+f"(d[10]), "+f"(d[11]), "+f"(d[12]), "+f"(d[13]), "+f"(d[14]), "+f"(d[15]),
        "+f"(d[16]), "+f"(d[17]), "+f"(d[18]), "+f"(d[19]), "+f"(d[20]), "+f"(d[21]), "+f"(d[22]), "+f"(d[23])
      : "r"(a[0]), "r"(a[1]), "r"(a[2]), "r"(a[3]), "l"(desc), "n"(ACC));
}
DEVI void pin(float (&d)[24]) {
#pragma unroll
  for (int i = 0; i < 24; ++i) asm volatile("" : "+f"(d[i]) :: "memory");
}

template <int OFF>
DEVI void st128(uint64_t p, int on, uint32_t a, uint32_t b, uint32_t c, uint32_t d) {
  asm volatile("{\n.reg .pred p;\nsetp.gt.s32 p, %5, 0;\n@p st.global.v4.b32 [%0+%6], {%1,%2,%3,%4};\n}\n"
               ::"l"(p), "r"(a), "r"(b), "r"(c), "r"(d), "r"(on), "n"(OFF) : "memory");
}
template <int OFF>
DEVI void st64(uint64_t p, int on, uint32_t a, uint32_t b) {
  asm volatile("{\n.reg .pred p;\nsetp.gt.s32 p, %3, 0;\n@p st.global.v2.b32 [%0+%4], {%1,%2};\n}\n"
               ::"l"(p), "r"(a), "r"(b), "r"(on), "n"(OFF) : "memory");
}

__global__ void __cluster_dims__(2, 1, 1) __launch_bounds__(NUM_THREADS, 1)
conv3x3_kernel(const __grid_constant__ CUtensorMap xmap, const __grid_constant__ CUtensorMap wmap,
               const uint8_t* __restrict__ xin, const uint8_t* __restrict__ wgt,
               const __nv_bfloat16* __restrict__ bias, __nv_bfloat16* __restrict__ out, uint32_t zero, uint32_t zero2) {
  extern __shared__ __align__(1024) uint8_t smem_raw[];
  if (threadIdx.x < 11) asm volatile("prefetch.global.L2 [%0];" ::"l"(wgt + min((blockIdx.x * 11 + threadIdx.x) * 128, 3 * W_RAW - 128)));
  const uint32_t sbase = smem_u32(smem_raw);
  const uint32_t bars = sbase + BAR_OFF;
  const int tid = threadIdx.x, warp = __shfl_sync(0xffffffffu, tid >> 5, 0), lane = tid & 31;
  const int half = blockIdx.x & 1, pair = blockIdx.x >> 1;
  const int off64 = half * 128, off32 = 64 + half * 32;
  const int line0 = (pair & 7) * 96 - 2, mid = (pair >> 3) * (4 * NB) + 2 * NB;

  auto xpf = [&](int k) {
    const int line = line0 + tid - 128 * k;
    if (tid >= 128 * k && tid < 128 * k + 100 && line >= 0 && line < OROW / 128)
      asm volatile("prefetch.global.L2 [%0];" ::"l"(xin + (size_t)(mid - 2 * k + half) * OROW + line * 128));
  };
  if (warp == 11) {
    if (elect_one()) {
#pragma unroll
      for (int i = 0; i < 11; ++i) mbar_init(bars + 8 * i, 1);
      asm volatile("fence.mbarrier_init.release.cluster;" ::: "memory");
      proxy_fence();
#pragma unroll
      for (int i = 0; i < 3; ++i) {
        if (i == 2) {
          mbar_expect_tx(bars, 2 * ROW_TX);
          tma_row(sbase, &xmap, line0, mid, bars);
          tma_row(sbase + ROW_PITCH, &xmap, line0, mid + 1, bars);
        }
        mbar_expect_tx(bars + 64 + 8 * i, W_RAW);
        tma_row(sbase + RING_BYTES + ((i + 1) % 3) * W_RAW, &wmap, 48 * i, 0, bars + 64 + 8 * i);
      }
    }
  }
  if ((sbase & 0xFFFFFFu) != SMEM_BASE) __trap();
  const uint4 bias_v = __ldg(reinterpret_cast<const uint4*>(bias + off64 / 2 + 8 * (lane & 3)));
  const uint2 bias_u = __ldg(reinterpret_cast<const uint2*>(bias + off32 / 2 + 4 * (lane & 3)));
  if (warp < 4) __nanosleep(150);
  xpf(0);
  float Z0[24], Z1[24], Z2[24], Z3[24];
  if (warp < 8) {
    const uint32_t r[6] = {bias_v.x, bias_v.y, bias_v.z, bias_v.w, bias_u.x, bias_u.y};
#pragma unroll
    for (int i = 0; i < 24; ++i) {
      const float b = (i & 1) ? bf_hi(r[i >> 2]) : bf_lo(r[i >> 2]), z = __uint_as_float(zero);
      Z0[i] = fadd(z, z); Z1[i] = fadd(b, b); Z2[i] = fadd(z, z); Z3[i] = fadd(z, z);
    }
  }
  __syncthreads();
  xpf(1);
  asm volatile("barrier.cluster.arrive.relaxed.aligned;" ::: "memory");
  {
    const int p = 16 * (warp & 3) + 2 * (lane & 7) - 1 + (lane >> 3);
    const uint32_t off = 192 * p + 256 + 64 * (warp >> 2), a0 = sbase + (off ^ (((off >> 7) & 7) << 4));
    asm volatile("st.shared.v4.b32 [%0], {%1,%2,%3,%4};" ::"r"(sbase + LA_OFF + tid * 16), "r"(a0), "r"(a0 ^ 16), "r"(a0 ^ 32), "r"(a0 ^ 48) : "memory");
  }
  auto w_fetch = [&](uint32_t (&raw)[3][6], uint32_t src) {
#pragma unroll
    for (int kh = 0; kh < 3; ++kh) {
      asm volatile("ld.shared.v4.b32 {%0,%1,%2,%3}, [%4];" : "=r"(raw[kh][0]), "=r"(raw[kh][1]), "=r"(raw[kh][2]), "=r"(raw[kh][3])
                   : "r"(src + kh * 3 * W_TAP + off64 + 16 * (lane & 3)) : "memory");
      asm volatile("ld.shared.v2.b32 {%0,%1}, [%2];" : "=r"(raw[kh][4]), "=r"(raw[kh][5])
                   : "r"(src + kh * 3 * W_TAP + off32 + 8 * (lane & 3)) : "memory");
    }
  };
  auto w_store = [&](const uint32_t (&raw)[3][6], uint32_t blk) {
    const uint32_t d4 = blk + lane * 16;
    const uint32_t d2 = blk + 512 + (lane & 15) * 16 + (lane >> 4) * (2 * W_SLOT);
    stsm4(d4, raw[0][0], raw[0][1], raw[0][2], raw[0][3]);
    stsm4(d4 + 2 * W_SLOT, raw[2][0], raw[2][1], raw[2][2], raw[2][3]);
    stsm4(d2, raw[0][4], raw[0][5], raw[2][4], raw[2][5]);
    uint32_t u1[6], u2[6];
#pragma unroll
    for (int j = 0; j < 6; ++j) {
      auto lo = [&](uint32_t v) { return __uint_as_float(v * (65536u + zero)); };
      const float tl = lo(raw[0][j]) + lo(raw[2][j]), th = bf_hi(raw[0][j]) + bf_hi(raw[2][j]);
      const float ml = lo(raw[1][j]), mh = bf_hi(raw[1][j]);
      u1[j] = pack_bf16(tl + ml, th + mh);
      u2[j] = pack_bf16(tl - ml, th - mh);
    }
    stsm4(d4 + W_SLOT, u1[0], u1[1], u1[2], u1[3]);
    stsm4(d4 + 3 * W_SLOT, u2[0], u2[1], u2[2], u2[3]);
    stsm4(d2 + W_SLOT, u1[4], u1[5], u2[4], u2[5]);
  };
  const uint32_t w_src = sbase + RING_BYTES + ((warp & 3) * 8 + (lane >> 2)) * 192, w_dst = sbase + W_OFF + (warp & 3) * 768;
#pragma unroll 1
  for (int i = 0; i < 2; ++i) {
    uint32_t raw[3][6];
    mbar_wait(bars + 64 + 8 * i, 0);
    w_fetch(raw, w_src + (i + 1) * W_RAW + (warp >> 2) * W_TAP);
    __syncthreads();
    w_store(raw, w_dst + i * W_3RD + (warp >> 2) * W_KW);
  }
  proxy_fence();
  asm volatile("barrier.cluster.wait.aligned;" ::: "memory");
  __syncthreads();

  if (warp >= 8) {
    asm volatile("setmaxnreg.dec.sync.aligned.u32 56;");
    if (warp < 10) {
      const int w = warp - 8, dir = 1 - 2 * w;
      const int ybase = mid - w;
      uint32_t peer_free;
      asm volatile("mapa.shared::cluster.u32 %0, %1, %2;" : "=r"(peer_free) : "r"(bars + 32 + 16 * w), "r"(half ^ 1));
      auto fill = [&](int slot, int y, int dy) {
        if (elect_one()) {
          mbar_expect_tx(bars + 8 * slot, 2 * ROW_TX);
          tma_row(sbase + slot * STAGE_BYTES, &xmap, line0, y, bars + 8 * slot);
          tma_row(sbase + slot * STAGE_BYTES + ROW_PITCH, &xmap, line0, y + dy, bars + 8 * slot);
        }
      };
      if (w == 1) fill(1, mid + 2, 1);
#pragma unroll 1
      for (int t = 0; t <= NB; ++t) {
        mbar_wait(bars + w * 16 + (t & 1) * 8, (t >> 1) & 1);
        if (t * w == 1) asm volatile("bar.sync 4, 96;" ::: "memory");
        asm volatile("bar.sync %0, 288;" ::"r"(2 - w) : "memory");
        if (t + w == 0) { fill(2, mid - 1, -1); fill(3, mid - 3, -1); }
        if (t < NB) asm volatile("bar.sync %0, 160;" ::"r"(6 + w) : "memory");
        const int tn = t + 2;
        const uint32_t dst = sbase + w * RING_BYTES + (tn & 1) * STAGE_BYTES, fb = bars + w * 16 + (tn & 1) * 8;
        if (tn < NB) {
          if (elect_one()) {
            mbar_expect_tx(fb, 2 * ROW_TX);
            asm volatile("mbarrier.arrive.relaxed.cluster.shared::cluster.b64 _, [%0];" ::"r"(peer_free + (t & 1) * 8) : "memory");
          }
          mbar_wait(bars + 32 + 16 * w + (t & 1) * 8, (t >> 1) & 1);
          if (elect_one()) tma_row_both(dst + half * ROW_PITCH, &xmap, line0, ybase + dir * (2 * tn + half), fb);
        } else if (tn == NB && elect_one()) {
          mbar_expect_tx(fb, ROW_TX);
          tma_row(dst, &xmap, line0, ybase + dir * 2 * NB, fb);
        }
        if (tn >= PF_START && 2 * (tn + PF_DIST) + half < 2 * NB && elect_one()) tma_row_prefetch(&xmap, line0, ybase + dir * (2 * (tn + PF_DIST) + half));
      }
    } else {
      const int h = warp - 10;
      const uint32_t xch = sbase + XCH_OFF + lane * 16;
      uint32_t v[4][2][4];
      asm volatile("bar.sync 3, 192;" ::: "memory");
#pragma unroll
      for (int w = 0; w < 4; ++w) {
#pragma unroll
        for (int n = 0; n < 2; ++n) {
          asm volatile("ld.shared.v4.b32 {%0,%1,%2,%3}, [%4];" : "=r"(v[w][n][0]), "=r"(v[w][n][1]), "=r"(v[w][n][2]), "=r"(v[w][n][3])
                       : "r"(xch + (3 * h + n) * 2048 + w * 512) : "memory");
        }
      }
      asm volatile("bar.arrive 4, 96;" ::: "memory");
      asm volatile("bar.sync 3, 192;" ::: "memory");
      const uint64_t p16 = (uint64_t)__cvta_generic_to_global(out) + (size_t)(mid - h) * OROW + ((pair & 7) * 64 + 2 * (lane >> 2)) * (CH * 2) + off64 + 16 * (lane & 3);
      const uint64_t p8 = p16 + (int64_t)(off32 - off64 - 8 * (lane & 3));
#pragma unroll
      for (int w = 0; w < 4; ++w) {
#pragma unroll
        for (int n = 0; n < 3; ++n) {
          __nanosleep(400);
          uint32_t a, b, c, d, q[4];
          if (n < 2) {
            asm volatile("ld.shared.v4.b32 {%0,%1,%2,%3}, [%4];" : "=r"(a), "=r"(b), "=r"(c), "=r"(d) : "r"(xch + (3 * (1 - h) + n) * 2048 + w * 512) : "memory");
            q[0] = v[w][n & 1][0]; q[1] = v[w][n & 1][1]; q[2] = v[w][n & 1][2]; q[3] = v[w][n & 1][3];
          } else {
            asm volatile("ld.shared.v4.b32 {%0,%1,%2,%3}, [%4];" : "=r"(a), "=r"(b), "=r"(c), "=r"(d) : "r"(sbase + ROW_TX + (w + 4 * (1 - h)) * ROW_PITCH + lane * 16) : "memory");
            asm volatile("ld.shared.v4.b32 {%0,%1,%2,%3}, [%4];" : "=r"(q[0]), "=r"(q[1]), "=r"(q[2]), "=r"(q[3]) : "r"(xch + (3 * h + 2) * 2048 + w * 512) : "memory");
          }
          a = hadd2(a, q[0]); b = hadd2(b, q[1]); c = hadd2(c, q[2]); d = hadd2(d, q[3]);
          if (n == 0) st128<0>(p16 + w * 3072, 1, a, b, c, d);
          if (n == 1) st128<192>(p16 + w * 3072, 1, a, b, c, d);
          if (n == 2) { st64<0>(p8 + w * 3072, 1, a, b); st64<192>(p8 + w * 3072, 1, c, d); }
        }
      }
    }
  } else {
    asm volatile("setmaxnreg.inc.sync.aligned.u32 224;");
    const int wg = warp >> 2, w = warp & 3;
    const int g = lane >> 2, t4 = lane & 3;
    if (wg == 1) {
      uint32_t raw[3][3][6];
      mbar_wait(bars + 80, 0);
#pragma unroll
      for (int kw = 0; kw < 3; ++kw) w_fetch(raw[kw], w_src + kw * W_TAP);
      proxy_fence();
      asm volatile("bar.arrive 2, 288;" ::: "memory");
#pragma unroll
      for (int kw = 0; kw < 3; ++kw) w_store(raw[kw], w_dst + 2 * W_3RD + kw * W_KW);
      proxy_fence();
      asm volatile("bar.arrive 5, 256;" ::: "memory");
    }

    uint32_t la[12];
#pragma unroll
    for (int q = 0; q < 3; ++q)
      asm volatile("ld.shared.v4.b32 {%0,%1,%2,%3}, [%4];" : "=r"(la[4 * q]), "=r"(la[4 * q + 1]), "=r"(la[4 * q + 2]), "=r"(la[4 * q + 3])
                   : "r"(sbase + LA_OFF + q * 2048 + (tid & 127) * 16) : "memory");
    uint32_t soff = wg * RING_BYTES;
    float b2[12];
    {
      const uint32_t r[6] = {bias_v.x, bias_v.y, bias_v.z, bias_v.w, bias_u.x, bias_u.y};
#pragma unroll
      for (int j = 0; j < 6; ++j) { b2[2 * j] = 2.f * bf_lo(r[j]); b2[2 * j + 1] = 2.f * bf_hi(r[j]); }
    }
    const int orow = wg ? -OROW : OROW;
    uint64_t op16 = (uint64_t)__cvta_generic_to_global(out) + (ptrdiff_t)(mid - wg) * OROW - (ptrdiff_t)orow
                    + ((pair & 7) * 64 + 16 * w + 2 * g) * (CH * 2) + off64 + 16 * t4;
    uint64_t op8 = op16 + (int64_t)(off32 - off64 - 8 * t4);
    op16 -= 2 * (int64_t)orow; op8 -= 2 * (int64_t)orow;
    uint64_t oq16 = op16 + orow, oq8 = op8 + orow;
    const int64_t ostep = 2 * (int64_t)orow;
    auto advance = [&](uint64_t& p) { asm volatile("add.s64 %0, %0, %1;" : "+l"(p) : "l"(ostep)); };
    const uint64_t dswap = wg ? (uint64_t)((2 * W_SLOT) >> 4) : 0;

    constexpr int NAB = LDA + 2;
    uint32_t A[NAB][4], B[NAB][4], S[3][4], D[3][4], MP[3][4], MQ[3][4];
    auto store = [&](const uint32_t (&y)[12], int n, int on, uint64_t p16, uint64_t p8) {
      if (n == 0) st128<0>(p16, on, y[0], y[1], y[2], y[3]);
      if (n == 1) st128<192>(p16, on, y[6], y[7], y[8], y[9]);
      if (n == 2) st64<0>(p8, on, y[4], y[5]);
      if (n == 3) st64<192>(p8, on, y[10], y[11]);
    };
    auto load = [&](int cg) { ldsm4(A[cg % NAB], la[cg] + soff); ldsm4(B[cg % NAB], la[cg] + soff + ROW_PITCH); };
    const uint32_t vzero = __shfl_sync(0xffffffffu, (uint32_t)tid & zero2, lane);
    uint32_t clk = 0;
    auto prep = [&](int r) {
#pragma unroll
      for (int i = 0; i < 4; ++i) {
        const int src = ((r - 1) & ~1) + (i >> 1), k = 1 + (i & 1);
        if (r < 12) S[r % 3][i] = hadd2(A[r % NAB][i], B[r % NAB][i]);
        if (r > 0) MP[r % 3][i] = copy32((r & 1) ? A[src % NAB][k] : S[src % 3][k], zero2);
        if (r < 12) D[r % 3][i] = hsub2(A[r % NAB][i], B[r % NAB][i]);
        if (r > 0) {
          const uint32_t v = (r & 1) ? B[src % NAB][k] : D[src % 3][k];
          if (i == 3 && r >= 2) asm volatile("lop3.b32 %0, %1, %2, %3, 0xF8;" : "=r"(MQ[r % 3][i]) : "r"(v), "r"(clk), "r"(vzero));
          else MQ[r % 3][i] = copy32(v, zero2);
        }
      }
    };

#pragma unroll
    for (int i = 0; i < 4; ++i) { A[11 % NAB][i] = 0; B[11 % NAB][i] = 0; S[11 % 3][i] = 0; D[11 % 3][i] = 0; MP[12 % 3][i] = 0; MQ[12 % 3][i] = 0; }

    for (int t = 0; t < NB; ++t) {
      uint32_t yo[12], ye[12];
#pragma unroll
      for (int i = 0; i < 4; ++i) {
        yo[i] = A[11 % NAB][i]; yo[6 + i] = B[11 % NAB][i]; ye[i] = S[11 % 3][i]; ye[6 + i] = D[11 % 3][i];
        yo[4 + (i & 1) + 6 * (i >> 1)] = MP[12 % 3][i]; ye[4 + (i & 1) + 6 * (i >> 1)] = MQ[12 % 3][i];
      }
      auto block = [&](int k) {
        if (t > (int)((k & 1) ? zero : zero2)) {
          float ev[2];
#pragma unroll
          for (int u = 0; u < 2; ++u) {
            const int e = k / 6, j = k % 6, i = 4 * j + 2 * e + u;
            if (u == 0) yo[k] = pack_bf16(Z0[i], Z0[i + 1]);
            const float sm = Z1[i] + Z2[i], df = Z1[i] - Z2[i];
            const float p = fmaf(0.5f, sm, -Z0[i]);
            ev[u] = fmaf(0.5f, df, -Z3[i]);
            Z0[i] = p;
            Z1[i] = (p + b2[2 * j + u]) + Z3[i];
            Z2[i] = p - Z3[i];
            if (u == 1) ye[k] = pack_bf16(ev[0], ev[1]);
            if (j == 3 && u == 0) store(yo, e, t - 1, op16, op8);
            if (j == 4 && u == 0) store(ye, e, t - 1, oq16, oq8);
            if (j == 5 && u == 0) store(yo, 2 + e, t - 1, op16, op8);
            if (j == 5 && u == 1) store(ye, 2 + e, t - 1, oq16, oq8);
            if (k == 0 && u == 0) { advance(op16); advance(op8); }
            if (k == 1 && u == 0) { advance(oq16); advance(oq8); }
          }
        }
      };
      if (t > 0) {
#pragma unroll
        for (int k = 0; k < 10; ++k) block(k);
      }
      soff = wg * RING_BYTES + (t & 1) * STAGE_BYTES;
      if (wg) asm volatile("bar.sync 1, 288;" ::: "memory"); else asm volatile("bar.sync 2, 288;" ::: "memory");
      static_assert(LDA == 3, "three channel groups are loaded ahead of the main loop");
      load(0);
      block(10);
      load(1);
      block(11);
      if (t == 1) {
        const uint32_t xch = sbase + XCH_OFF + (tid & 127) * 16;
        auto put = [&](int n, uint32_t a, uint32_t b, uint32_t c, uint32_t d) {
          asm volatile("st.shared.v4.b32 [%0], {%1,%2,%3,%4};" ::"r"(xch + n * 2048), "r"(a), "r"(b), "r"(c), "r"(d) : "memory");
        };
        put(0, ye[0], ye[1], ye[2], ye[3]); put(1, ye[6], ye[7], ye[8], ye[9]);
        put(3, yo[0], yo[1], yo[2], yo[3]); put(4, yo[6], yo[7], yo[8], yo[9]);
        const uint32_t x2 = wg ? sbase + ROW_TX + w * ROW_PITCH + lane * 16 : xch + 2 * 2048, x5 = x2 + (wg ? 4 * ROW_PITCH : 3 * 2048);
        asm volatile("st.shared.v4.b32 [%0], {%1,%2,%3,%4};" ::"r"(x2), "r"(ye[4]), "r"(ye[5]), "r"(ye[10]), "r"(ye[11]) : "memory");
        asm volatile("st.shared.v4.b32 [%0], {%1,%2,%3,%4};" ::"r"(x5), "r"(yo[4]), "r"(yo[5]), "r"(yo[10]), "r"(yo[11]) : "memory");
        asm volatile("bar.arrive 3, 192;" ::: "memory");
      }
      load(2);
      prep(0);
      const uint64_t dbase = WDESC + (uint64_t)(t & zero), db0 = dbase - dswap, db3 = dbase + dswap;
      wg_fence();
#pragma unroll
      for (int r = 0; r < 13; ++r) {
        if (r < 12) {
          mma48<1>(Z0, A[r % NAB], db0, d_outer(r, 0));
          mma48<1>(Z1, S[r % 3], dbase, d_outer(r, 1));
          mma48<1>(Z2, D[r % 3], dbase, d_outer(r, 2));
          if (r == 0) mma48<0>(Z3, B[r % NAB], db3, d_outer(r, 3));
          else mma48<1>(Z3, B[r % NAB], db3, d_outer(r, 3));
        }
        if (r > 0) {
          const int c = (r - 1) >> 1;
          if (r & 1) { mma48<1>(Z0, MP[r % 3], db0, d_mid(c, 0)); mma48<1>(Z3, MQ[r % 3], db3, d_mid(c, 3)); }
          else       { mma48<1>(Z1, MP[r % 3], dbase, d_mid(c, 1)); mma48<1>(Z2, MQ[r % 3], dbase, d_mid(c, 2)); }
        }
        wg_commit();
        if (r + LDA < 12) load(r + LDA);
        if (r == GATE_R) asm volatile("bar.arrive %0, 288;" ::"r"(1 + wg) : "memory");
        if (r == 11) asm volatile("bar.arrive %0, 160;" ::"r"(6 + wg) : "memory");
        if (r < 12) {
          prep(r + 1);
          if (r == 7 && t + wg == 0) asm volatile("bar.sync 5, 256;" ::: "memory");
          wg_fence();
          wg_wait<1>();
          if (r < 11) asm volatile("mov.u32 %0, %clock;" : "=r"(clk) :: "memory");
        } else {
          wg_wait<0>();
        }
      }
      pin(Z0); pin(Z1); pin(Z2); pin(Z3);
    }
    advance(op16); advance(op8);

    {
      uint32_t yo[12], ye[12], F[12][4], M[6][4];
      float T[24];
      auto rows = [&]() {
#pragma unroll
        for (int k = 0; k < 12; ++k) yo[k] = pack_bf16(Z0[4 * (k % 6) + 2 * (k / 6)], Z0[4 * (k % 6) + 2 * (k / 6) + 1]);
#pragma unroll
        for (int n = 0; n < 4; ++n) store(yo, n, 1, op16, op8);
#pragma unroll
        for (int j = 0; j < 6; ++j) {
          sched_fence();
          float ev[4];
#pragma unroll
          for (int u = 0; u < 4; ++u) {
            const int i = 4 * j + u;
            ev[u] = fmah(fsub(Z1[i], Z2[i]), Z3[i]);
            Z0[i] = fmah(fadd(Z1[i], Z2[i]), Z0[i]);
          }
          ye[j] = pack_bf16(ev[0], ev[1]); ye[6 + j] = pack_bf16(ev[2], ev[3]);
          if (j == 3) { store(ye, 0, 1, op16 + orow, op8 + orow); store(ye, 1, 1, op16 + orow, op8 + orow); }
          if (j == 5) { store(ye, 2, 1, op16 + orow, op8 + orow); store(ye, 3, 1, op16 + orow, op8 + orow); }
        }
        sched_fence();
      };
      if (wg == 0) {
        rows();
        asm volatile("bar.sync 2, 288;" ::: "memory");
        asm volatile("bar.arrive 1, 288;" ::: "memory");
      } else {
        asm volatile("bar.sync 1, 288;" ::: "memory");
      }
#pragma unroll
      for (int cg = 0; cg < 12; ++cg) ldsm4(F[cg], la[cg] + wg * RING_BYTES + (NB & 1) * STAGE_BYTES);
      const uint64_t d0 = WDESC - dswap + zero2;
#pragma unroll
      for (int c = 0; c < 6; ++c) {
        M[c][0] = copy32(F[2 * c][1], zero2); M[c][1] = copy32(F[2 * c][2], zero2);
        M[c][2] = copy32(F[2 * c + 1][1], zero2); M[c][3] = copy32(F[2 * c + 1][2], zero2);
      }
      wg_fence();
#pragma unroll
      for (int c = 0; c < 6; ++c) {
        if (c == 0) mma48<0>(T, F[0], d0, d_outer(0, 0));
        else mma48<1>(T, F[2 * c], d0, d_outer(2 * c, 0));
        mma48<1>(T, F[2 * c + 1], d0, d_outer(2 * c + 1, 0));
        mma48<1>(T, M[c], d0, d_mid(c, 0));
      }
      wg_commit();
      if (wg == 1) rows();
      wg_wait<0>();
      pin(T);
#pragma unroll
      for (int k = 0; k < 12; ++k) {
        const int i = 4 * (k % 6) + 2 * (k / 6);
        yo[k] = pack_bf16(Z0[i] + T[i], Z0[i + 1] + T[i + 1]);
      }
#pragma unroll
      for (int n = 0; n < 4; ++n) store(yo, n, 1, op16 + 2 * orow, op8 + 2 * orow);
    }
  }
}

typedef CUresult (*EncodeTiledFn)(CUtensorMap*, CUtensorMapDataType, cuuint32_t, void*, const cuuint64_t*,
                                  const cuuint64_t*, const cuuint32_t*, const cuuint32_t*, CUtensorMapInterleave,
                                  CUtensorMapSwizzle, CUtensorMapL2promotion, CUtensorMapFloatOOBfill);

}

extern "C" void kernel_launch(void* const* d_in, const int* in_sizes, int n_in, void* d_out, int out_size) {
  (void)in_sizes; (void)n_in; (void)out_size;
  static EncodeTiledFn encode = nullptr;
  if (!encode) {
    void* fn = nullptr;
    cudaDriverEntryPointQueryResult qr;
    cudaGetDriverEntryPoint("cuTensorMapEncodeTiled", &fn, cudaEnableDefault, &qr);
    encode = (EncodeTiledFn)fn;
    cudaFuncSetAttribute(conv3x3_kernel, cudaFuncAttributeMaxDynamicSharedMemorySize, SMEM_BYTES);
  }
  CUtensorMap xmap;
  const cuuint64_t dims[3] = {64, (cuuint64_t)(OROW / 128), (cuuint64_t)IMG_H};
  const cuuint64_t strides[2] = {128, (cuuint64_t)OROW};
  const cuuint32_t box[3] = {64, ROW_LINES, 1};
  const cuuint32_t estr[3] = {1, 1, 1};
  encode(&xmap, CU_TENSOR_MAP_DATA_TYPE_BFLOAT16, 3, d_in[0], dims, strides, box, estr, CU_TENSOR_MAP_INTERLEAVE_NONE,
         CU_TENSOR_MAP_SWIZZLE_128B, CU_TENSOR_MAP_L2_PROMOTION_L2_256B, CU_TENSOR_MAP_FLOAT_OOB_FILL_NONE);
  CUtensorMap wmap;
  const cuuint64_t wdims[3] = {64, CH * CH * 2 / 128, 9};
  const cuuint64_t wstrides[2] = {128, CH * CH * 2};
  const cuuint32_t wbox[3] = {64, W_TAP / 128, 9};
  encode(&wmap, CU_TENSOR_MAP_DATA_TYPE_BFLOAT16, 3, d_in[1], wdims, wstrides, wbox, estr, CU_TENSOR_MAP_INTERLEAVE_NONE,
         CU_TENSOR_MAP_SWIZZLE_NONE, CU_TENSOR_MAP_L2_PROMOTION_L2_256B, CU_TENSOR_MAP_FLOAT_OOB_FILL_NONE);
  conv3x3_kernel<<<128, NUM_THREADS, SMEM_BYTES, cudaStreamPerThread>>>(
      xmap, wmap, (const uint8_t*)d_in[0], (const uint8_t*)d_in[1], (const __nv_bfloat16*)d_in[2], (__nv_bfloat16*)d_out, 0u, 0u);
}
```

```cpp
#include <cuda_runtime.h>
#include <cuda_bf16.h>
#include <cuda.h>
#include <stdint.h>

#define DEVI __device__ __forceinline__

namespace {

constexpr int IMG_H = 512, IMG_W = 512, CH = 96;
constexpr int OROW = IMG_W * CH * 2;
constexpr int NB = 16;
constexpr int ROW_LINES = 100;
constexpr int ROW_TX = ROW_LINES * 128;
constexpr int ROW_PITCH = 13312;
constexpr int STAGE_BYTES = 2 * ROW_PITCH;
constexpr int RING_BYTES = 2 * STAGE_BYTES;
constexpr int W_TAP = 32 * CH * 2;
constexpr int W_RAW = 9 * W_TAP;
constexpr int W_OFF = RING_BYTES + W_RAW;
constexpr int W_SLOT = 32 * 48 * 2;
constexpr int W_KW = 4 * W_SLOT;
constexpr int W_3RD = 3 * W_KW;
constexpr int BAR_OFF = W_OFF + 3 * W_3RD;
constexpr int LA_OFF = BAR_OFF + 128;
constexpr int XCH_OFF = LA_OFF;
constexpr int SMEM_BYTES = XCH_OFF + 12288;
constexpr uint32_t SMEM_BASE = 1024;
constexpr int NUM_THREADS = 384;
constexpr int LDA = 3;
constexpr int GATE_R = 8;
constexpr int PF_START = 5, PF_DIST = 1;

constexpr uint64_t WDESC = (uint64_t)((SMEM_BASE + W_OFF) >> 4) | ((uint64_t)(128 >> 4) << 32);
__host__ __device__ constexpr int w_slot(int pos) { return pos == 0 ? 2 : pos == 1 ? 1 : pos == 2 ? 3 : 0; }
__host__ __device__ constexpr uint32_t d_outer(int cg, int pos) { return (uint32_t)((((cg >> 2) * W_3RD + w_slot(pos) * W_SLOT + (cg & 3) * 768) >> 4) | (((2 * W_KW) >> 4) << 16)); }
__host__ __device__ constexpr uint32_t d_mid(int c, int pos) { return (uint32_t)((((c >> 1) * W_3RD + W_KW + w_slot(pos) * W_SLOT + (c & 1) * 1536) >> 4) | ((768 >> 4) << 16)); }

DEVI uint32_t smem_u32(const void* p) { return (uint32_t)__cvta_generic_to_shared(p); }
DEVI void wg_fence() { asm volatile("wgmma.fence.sync.aligned;" ::: "memory"); }
DEVI void wg_commit() { asm volatile("wgmma.commit_group.sync.aligned;" ::: "memory"); }
template <int N> DEVI void wg_wait() { asm volatile("wgmma.wait_group.sync.aligned %0;" ::"n"(N) : "memory"); }
DEVI void proxy_fence() { asm volatile("fence.proxy.async.shared::cta;" ::: "memory"); }
DEVI void sched_fence() { asm volatile("pmevent 0;" ::: "memory"); }

DEVI void ldsm4(uint32_t (&r)[4], uint32_t addr) {
  asm volatile("ldmatrix.sync.aligned.m8n8.x4.shared.b16 {%0,%1,%2,%3}, [%4];"
               : "=r"(r[0]), "=r"(r[1]), "=r"(r[2]), "=r"(r[3]) : "r"(addr) : "memory");
}
DEVI void stsm4(uint32_t addr, uint32_t r0, uint32_t r1, uint32_t r2, uint32_t r3) {
  asm volatile("stmatrix.sync.aligned.m8n8.x4.shared.b16 [%0], {%1,%2,%3,%4};"
               ::"r"(addr), "r"(r0), "r"(r1), "r"(r2), "r"(r3) : "memory");
}
DEVI uint32_t hadd2(uint32_t a, uint32_t b) { uint32_t r; asm volatile("add.rn.bf16x2 %0, %1, %2;" : "=r"(r) : "r"(a), "r"(b)); return r; }
DEVI uint32_t hsub2(uint32_t a, uint32_t b) { uint32_t r; asm volatile("sub.rn.bf16x2 %0, %1, %2;" : "=r"(r) : "r"(a), "r"(b)); return r; }
DEVI uint32_t copy32(uint32_t a, uint32_t z) { uint32_t r; asm volatile("or.b32 %0, %1, %2;" : "=r"(r) : "r"(a), "r"(z)); return r; }
DEVI uint32_t pack_bf16(float lo, float hi) { uint32_t r; asm("cvt.rn.bf16x2.f32 %0, %1, %2;" : "=r"(r) : "f"(hi), "f"(lo)); return r; }
DEVI float fadd(float a, float b) { float r; asm volatile("add.rn.f32 %0, %1, %2;" : "=f"(r) : "f"(a), "f"(b)); return r; }
DEVI float fsub(float a, float b) { float r; asm volatile("sub.rn.f32 %0, %1, %2;" : "=f"(r) : "f"(a), "f"(b)); return r; }
DEVI float fmah(float a, float b) { float r; asm volatile("fma.rn.f32 %0, %1, 0f3F000000, %2;" : "=f"(r) : "f"(a), "f"(-b)); return r; }
DEVI float bf_lo(uint32_t v) { return __uint_as_float(v << 16); }
DEVI float bf_hi(uint32_t v) { return __uint_as_float(v & 0xffff0000u); }

DEVI void mbar_init(uint32_t bar, uint32_t cnt) { asm volatile("mbarrier.init.shared::cta.b64 [%0], %1;" ::"r"(bar), "r"(cnt) : "memory"); }
DEVI void mbar_expect_tx(uint32_t bar, uint32_t tx) { asm volatile("mbarrier.arrive.expect_tx.shared::cta.b64 _, [%0], %1;" ::"r"(bar), "r"(tx) : "memory"); }
DEVI void mbar_wait(uint32_t bar, uint32_t parity) {
  asm volatile(
      "{\n.reg .pred p;\n.reg .u32 c;\n"
      "mbarrier.try_wait.parity.shared::cta.b64 p, [%0], %1;\n"
      "@p bra.uni DONE;\n"
      "mov.u32 c, 0;\n"
      "SPIN:\n"
      "mbarrier.try_wait.parity.shared::cta.b64 p, [%0], %1, 100000;\n"
      "@p bra.uni DONE;\n"
      "add.u32 c, c, 1;\n"
      "setp.lt.u32 p, c, 0x4000;\n"
      "@p bra.uni SPIN;\n"
      "DONE:\n}\n" ::"r"(bar), "r"(parity) : "memory");
}
DEVI bool elect_one() {
  uint32_t p;
  asm volatile("{\n.reg .pred p;\nelect.sync _|p, 0xffffffff;\nselp.b32 %0, 1, 0, p;\n}\n" : "=r"(p));
  return p != 0;
}
DEVI void tma_row(uint32_t dst, const CUtensorMap* map, int line, int y, uint32_t bar) {
  asm volatile("cp.async.bulk.tensor.3d.shared::cluster.global.mbarrier::complete_tx::bytes [%0], [%1, {%3, %4, %5}], [%2];"
               ::"r"(dst), "l"(map), "r"(bar), "r"(0), "r"(line), "r"(y) : "memory");
}
DEVI void tma_row_both(uint32_t dst, const CUtensorMap* map, int line, int y, uint32_t bar) {
  asm volatile("cp.async.bulk.tensor.3d.shared::cluster.global.mbarrier::complete_tx::bytes.multicast::cluster [%0], [%1, {%3, %4, %5}], [%2], %6;"
               ::"r"(dst), "l"(map), "r"(bar), "r"(0), "r"(line), "r"(y), "h"((uint16_t)3) : "memory");
}
DEVI void tma_row_prefetch(const CUtensorMap* map, int line, int y) {
  asm volatile("cp.async.bulk.prefetch.tensor.3d.L2.global [%0, {%1, %2, %3}];" ::"l"(map), "r"(0), "r"(line), "r"(y) : "memory");
}

template <int ACC>
DEVI void mma48(float (&d)[24], const uint32_t (&a)[4], uint64_t dbase, uint32_t doff) {
  const uint64_t desc = dbase + (uint64_t)doff;
  asm volatile(
      "wgmma.mma_async.sync.aligned.m64n48k16.f32.bf16.bf16 "
      "{%0,%1,%2,%3,%4,%5,%6,%7,%8,%9,%10,%11,%12,%13,%14,%15,%16,%17,%18,%19,%20,%21,%22,%23}, "
      "{%24,%25,%26,%27}, %28, %29, 1, 1, 1;\n"
      : "+f"(d[0]), "+f"(d[1]), "+f"(d[2]), "+f"(d[3]), "+f"(d[4]), "+f"(d[5]), "+f"(d[6]), "+f"(d[7]),
        "+f"(d[8]), "+f"(d[9]), "+f"(d[10]), "+f"(d[11]), "+f"(d[12]), "+f"(d[13]), "+f"(d[14]), "+f"(d[15]),
        "+f"(d[16]), "+f"(d[17]), "+f"(d[18]), "+f"(d[19]), "+f"(d[20]), "+f"(d[21]), "+f"(d[22]), "+f"(d[23])
      : "r"(a[0]), "r"(a[1]), "r"(a[2]), "r"(a[3]), "l"(desc), "n"(ACC));
}
DEVI void pin(float (&d)[24]) {
#pragma unroll
  for (int i = 0; i < 24; ++i) asm volatile("" : "+f"(d[i]) :: "memory");
}

template <int OFF>
DEVI void st128(uint64_t p, int on, uint32_t a, uint32_t b, uint32_t c, uint32_t d) {
  asm volatile("{\n.reg .pred p;\nsetp.gt.s32 p, %5, 0;\n@p st.global.v4.b32 [%0+%6], {%1,%2,%3,%4};\n}\n"
               ::"l"(p), "r"(a), "r"(b), "r"(c), "r"(d), "r"(on), "n"(OFF) : "memory");
}
template <int OFF>
DEVI void st64(uint64_t p, int on, uint32_t a, uint32_t b) {
  asm volatile("{\n.reg .pred p;\nsetp.gt.s32 p, %3, 0;\n@p st.global.v2.b32 [%0+%4], {%1,%2};\n}\n"
               ::"l"(p), "r"(a), "r"(b), "r"(on), "n"(OFF) : "memory");
}

__global__ void __cluster_dims__(2, 1, 1) __launch_bounds__(NUM_THREADS, 1)
conv3x3_kernel(const __grid_constant__ CUtensorMap xmap, const __grid_constant__ CUtensorMap wmap,
               const uint8_t* __restrict__ xin, const uint8_t* __restrict__ wgt,
               const __nv_bfloat16* __restrict__ bias, __nv_bfloat16* __restrict__ out, uint32_t zero, uint32_t zero2) {
  extern __shared__ __align__(1024) uint8_t smem_raw[];
  if (threadIdx.x < 11) asm volatile("prefetch.global.L2 [%0];" ::"l"(wgt + min((blockIdx.x * 11 + threadIdx.x) * 128, 3 * W_RAW - 128)));
  const uint32_t sbase = smem_u32(smem_raw);
  const uint32_t bars = sbase + BAR_OFF;
  const int tid = threadIdx.x, warp = __shfl_sync(0xffffffffu, tid >> 5, 0), lane = tid & 31;
  const int half = blockIdx.x & 1, pair = blockIdx.x >> 1;
  const int off64 = half * 128, off32 = 64 + half * 32;
  const int line0 = (pair & 7) * 96 - 2, mid = (pair >> 3) * (4 * NB) + 2 * NB;

  auto xpf = [&](int k) {
    const int line = line0 + tid - 128 * k;
    if (tid >= 128 * k && tid < 128 * k + 100 && line >= 0 && line < OROW / 128)
      asm volatile("prefetch.global.L2 [%0];" ::"l"(xin + (size_t)(mid - 2 * k + half) * OROW + line * 128));
  };
  if (warp == 11) {
    if (elect_one()) {
#pragma unroll
      for (int i = 0; i < 11; ++i) mbar_init(bars + 8 * i, 1);
      asm volatile("fence.mbarrier_init.release.cluster;" ::: "memory");
      proxy_fence();
#pragma unroll
      for (int i = 0; i < 3; ++i) {
        if (i == 2) {
          mbar_expect_tx(bars, 2 * ROW_TX);
          tma_row(sbase, &xmap, line0, mid, bars);
          tma_row(sbase + ROW_PITCH, &xmap, line0, mid + 1, bars);
        }
        mbar_expect_tx(bars + 64 + 8 * i, W_RAW);
        tma_row(sbase + RING_BYTES + ((i + 1) % 3) * W_RAW, &wmap, 48 * i, 0, bars + 64 + 8 * i);
      }
    }
  }
  if ((sbase & 0xFFFFFFu) != SMEM_BASE) __trap();
  const uint4 bias_v = __ldg(reinterpret_cast<const uint4*>(bias + off64 / 2 + 8 * (lane & 3)));
  const uint2 bias_u = __ldg(reinterpret_cast<const uint2*>(bias + off32 / 2 + 4 * (lane & 3)));
  if (warp < 4) __nanosleep(150);
  xpf(0);
  float Z0[24], Z1[24], Z2[24], Z3[24];
  if (warp < 8) {
    const uint32_t r[6] = {bias_v.x, bias_v.y, bias_v.z, bias_v.w, bias_u.x, bias_u.y};
#pragma unroll
    for (int i = 0; i < 24; ++i) {
      const float b = (i & 1) ? bf_hi(r[i >> 2]) : bf_lo(r[i >> 2]), z = __uint_as_float(zero);
      Z0[i] = fadd(z, z); Z1[i] = fadd(b, b); Z2[i] = fadd(z, z); Z3[i] = fadd(z, z);
    }
  }
  __syncthreads();
  xpf(1);
  asm volatile("barrier.cluster.arrive.relaxed.aligned;" ::: "memory");
  {
    const int p = 16 * (warp & 3) + 2 * (lane & 7) - 1 + (lane >> 3);
    const uint32_t off = 192 * p + 256 + 64 * (warp >> 2), a0 = sbase + (off ^ (((off >> 7) & 7) << 4));
    asm volatile("st.shared.v4.b32 [%0], {%1,%2,%3,%4};" ::"r"(sbase + LA_OFF + tid * 16), "r"(a0), "r"(a0 ^ 16), "r"(a0 ^ 32), "r"(a0 ^ 48) : "memory");
  }
  auto w_fetch = [&](uint32_t (&raw)[3][6], uint32_t src) {
#pragma unroll
    for (int kh = 0; kh < 3; ++kh) {
      asm volatile("ld.shared.v4.b32 {%0,%1,%2,%3}, [%4];" : "=r"(raw[kh][0]), "=r"(raw[kh][1]), "=r"(raw[kh][2]), "=r"(raw[kh][3])
                   : "r"(src + kh * 3 * W_TAP + off64 + 16 * (lane & 3)) : "memory");
      asm volatile("ld.shared.v2.b32 {%0,%1}, [%2];" : "=r"(raw[kh][4]), "=r"(raw[kh][5])
                   : "r"(src + kh * 3 * W_TAP + off32 + 8 * (lane & 3)) : "memory");
    }
  };
  auto w_store = [&](const uint32_t (&raw)[3][6], uint32_t blk) {
    const uint32_t d4 = blk + lane * 16;
    const uint32_t d2 = blk + 512 + (lane & 15) * 16 + (lane >> 4) * (2 * W_SLOT);
    stsm4(d4, raw[0][0], raw[0][1], raw[0][2], raw[0][3]);
    stsm4(d4 + 2 * W_SLOT, raw[2][0], raw[2][1], raw[2][2], raw[2][3]);
    stsm4(d2, raw[0][4], raw[0][5], raw[2][4], raw[2][5]);
    uint32_t u1[6], u2[6];
#pragma unroll
    for (int j = 0; j < 6; ++j) {
      auto lo = [&](uint32_t v) { return __uint_as_float(v * (65536u + zero)); };
      const float tl = lo(raw[0][j]) + lo(raw[2][j]), th = bf_hi(raw[0][j]) + bf_hi(raw[2][j]);
      const float ml = lo(raw[1][j]), mh = bf_hi(raw[1][j]);
      u1[j] = pack_bf16(tl + ml, th + mh);
      u2[j] = pack_bf16(tl - ml, th - mh);
    }
    stsm4(d4 + W_SLOT, u1[0], u1[1], u1[2], u1[3]);
    stsm4(d4 + 3 * W_SLOT, u2[0], u2[1], u2[2], u2[3]);
    stsm4(d2 + W_SLOT, u1[4], u1[5], u2[4], u2[5]);
  };
  const uint32_t w_src = sbase + RING_BYTES + ((warp & 3) * 8 + (lane >> 2)) * 192, w_dst = sbase + W_OFF + (warp & 3) * 768;
#pragma unroll 1
  for (int i = 0; i < 2; ++i) {
    uint32_t raw[3][6];
    mbar_wait(bars + 64 + 8 * i, 0);
    w_fetch(raw, w_src + (i + 1) * W_RAW + (warp >> 2) * W_TAP);
    __syncthreads();
    w_store(raw, w_dst + i * W_3RD + (warp >> 2) * W_KW);
  }
  proxy_fence();
  asm volatile("barrier.cluster.wait.aligned;" ::: "memory");
  __syncthreads();

  if (warp >= 8) {
    asm volatile("setmaxnreg.dec.sync.aligned.u32 56;");
    if (warp < 10) {
      const int w = warp - 8, dir = 1 - 2 * w;
      const int ybase = mid - w;
      uint32_t peer_free;
      asm volatile("mapa.shared::cluster.u32 %0, %1, %2;" : "=r"(peer_free) : "r"(bars + 32 + 16 * w), "r"(half ^ 1));
      auto fill = [&](int slot, int y, int dy) {
        if (elect_one()) {
          mbar_expect_tx(bars + 8 * slot, 2 * ROW_TX);
          tma_row(sbase + slot * STAGE_BYTES, &xmap, line0, y, bars + 8 * slot);
          tma_row(sbase + slot * STAGE_BYTES + ROW_PITCH, &xmap, line0, y + dy, bars + 8 * slot);
        }
      };
      if (w == 1) fill(1, mid + 2, 1);
#pragma unroll 1
      for (int t = 0; t <= NB; ++t) {
        mbar_wait(bars + w * 16 + (t & 1) * 8, (t >> 1) & 1);
        if (t * w == 1) asm volatile("bar.sync 4, 96;" ::: "memory");
        asm volatile("bar.sync %0, 288;" ::"r"(2 - w) : "memory");
        if (t + w == 0) { fill(2, mid - 1, -1); fill(3, mid - 3, -1); }
        if (t < NB) asm volatile("bar.sync %0, 160;" ::"r"(6 + w) : "memory");
        const int tn = t + 2;
        const uint32_t dst = sbase + w * RING_BYTES + (tn & 1) * STAGE_BYTES, fb = bars + w * 16 + (tn & 1) * 8;
        if (tn < NB) {
          if (elect_one()) {
            mbar_expect_tx(fb, 2 * ROW_TX);
            asm volatile("mbarrier.arrive.relaxed.cluster.shared::cluster.b64 _, [%0];" ::"r"(peer_free + (t & 1) * 8) : "memory");
          }
          mbar_wait(bars + 32 + 16 * w + (t & 1) * 8, (t >> 1) & 1);
          if (elect_one()) tma_row_both(dst + half * ROW_PITCH, &xmap, line0, ybase + dir * (2 * tn + half), fb);
        } else if (tn == NB && elect_one()) {
          mbar_expect_tx(fb, ROW_TX);
          tma_row(dst, &xmap, line0, ybase + dir * 2 * NB, fb);
        }
        if (tn >= PF_START && 2 * (tn + PF_DIST) + half < 2 * NB && elect_one()) tma_row_prefetch(&xmap, line0, ybase + dir * (2 * (tn + PF_DIST) + half));
      }
    } else {
      const int h = warp - 10;
      const uint32_t xch = sbase + XCH_OFF + lane * 16;
      uint32_t v[4][2][4];
      asm volatile("bar.sync 3, 192;" ::: "memory");
#pragma unroll
      for (int w = 0; w < 4; ++w) {
#pragma unroll
        for (int n = 0; n < 2; ++n) {
          asm volatile("ld.shared.v4.b32 {%0,%1,%2,%3}, [%4];" : "=r"(v[w][n][0]), "=r"(v[w][n][1]), "=r"(v[w][n][2]), "=r"(v[w][n][3])
                       : "r"(xch + (3 * h + n) * 2048 + w * 512) : "memory");
        }
      }
      asm volatile("bar.arrive 4, 96;" ::: "memory");
      asm volatile("bar.sync 3, 192;" ::: "memory");
      const uint64_t p16 = (uint64_t)__cvta_generic_to_global(out) + (size_t)(mid - h) * OROW + ((pair & 7) * 64 + 2 * (lane >> 2)) * (CH * 2) + off64 + 16 * (lane & 3);
      const uint64_t p8 = p16 + (int64_t)(off32 - off64 - 8 * (lane & 3));
#pragma unroll
      for (int w = 0; w < 4; ++w) {
#pragma unroll
        for (int n = 0; n < 3; ++n) {
          __nanosleep(400);
          uint32_t a, b, c, d, q[4];
          if (n < 2) {
            asm volatile("ld.shared.v4.b32 {%0,%1,%2,%3}, [%4];" : "=r"(a), "=r"(b), "=r"(c), "=r"(d) : "r"(xch + (3 * (1 - h) + n) * 2048 + w * 512) : "memory");
            q[0] = v[w][n & 1][0]; q[1] = v[w][n & 1][1]; q[2] = v[w][n & 1][2]; q[3] = v[w][n & 1][3];
          } else {
            asm volatile("ld.shared.v4.b32 {%0,%1,%2,%3}, [%4];" : "=r"(a), "=r"(b), "=r"(c), "=r"(d) : "r"(sbase + ROW_TX + (w + 4 * (1 - h)) * ROW_PITCH + lane * 16) : "memory");
            asm volatile("ld.shared.v4.b32 {%0,%1,%2,%3}, [%4];" : "=r"(q[0]), "=r"(q[1]), "=r"(q[2]), "=r"(q[3]) : "r"(xch + (3 * h + 2) * 2048 + w * 512) : "memory");
          }
          a = hadd2(a, q[0]); b = hadd2(b, q[1]); c = hadd2(c, q[2]); d = hadd2(d, q[3]);
          if (n == 0) st128<0>(p16 + w * 3072, 1, a, b, c, d);
          if (n == 1) st128<192>(p16 + w * 3072, 1, a, b, c, d);
          if (n == 2) { st64<0>(p8 + w * 3072, 1, a, b); st64<192>(p8 + w * 3072, 1, c, d); }
        }
      }
    }
  } else {
    asm volatile("setmaxnreg.inc.sync.aligned.u32 224;");
    const int wg = warp >> 2, w = warp & 3;
    const int g = lane >> 2, t4 = lane & 3;
    if (wg == 1) {
      uint32_t raw[3][3][6];
      mbar_wait(bars + 80, 0);
#pragma unroll
      for (int kw = 0; kw < 3; ++kw) w_fetch(raw[kw], w_src + kw * W_TAP);
      proxy_fence();
      asm volatile("bar.arrive 2, 288;" ::: "memory");
#pragma unroll
      for (int kw = 0; kw < 3; ++kw) w_store(raw[kw], w_dst + 2 * W_3RD + kw * W_KW);
      proxy_fence();
      asm volatile("bar.arrive 5, 256;" ::: "memory");
    }

    uint32_t la[12];
#pragma unroll
    for (int q = 0; q < 3; ++q)
      asm volatile("ld.shared.v4.b32 {%0,%1,%2,%3}, [%4];" : "=r"(la[4 * q]), "=r"(la[4 * q + 1]), "=r"(la[4 * q + 2]), "=r"(la[4 * q + 3])
                   : "r"(sbase + LA_OFF + q * 2048 + (tid & 127) * 16) : "memory");
    uint32_t soff = wg * RING_BYTES;
    float b2[12];
    {
      const uint32_t r[6] = {bias_v.x, bias_v.y, bias_v.z, bias_v.w, bias_u.x, bias_u.y};
#pragma unroll
      for (int j = 0; j < 6; ++j) { b2[2 * j] = 2.f * bf_lo(r[j]); b2[2 * j + 1] = 2.f * bf_hi(r[j]); }
    }
    const int orow = wg ? -OROW : OROW;
    uint64_t op16 = (uint64_t)__cvta_generic_to_global(out) + (ptrdiff_t)(mid - wg) * OROW - (ptrdiff_t)orow
                    + ((pair & 7) * 64 + 16 * w + 2 * g) * (CH * 2) + off64 + 16 * t4;
    uint64_t op8 = op16 + (int64_t)(off32 - off64 - 8 * t4);
    op16 -= 2 * (int64_t)orow; op8 -= 2 * (int64_t)orow;
    uint64_t oq16 = op16 + orow, oq8 = op8 + orow;
    const int64_t ostep = 2 * (int64_t)orow;
    auto advance = [&](uint64_t& p) { asm volatile("add.s64 %0, %0, %1;" : "+l"(p) : "l"(ostep)); };
    const uint64_t dswap = wg ? (uint64_t)((2 * W_SLOT) >> 4) : 0;

    constexpr int NAB = LDA + 2;
    uint32_t A[NAB][4], B[NAB][4], S[3][4], D[3][4], MP[3][4], MQ[3][4];
    auto store = [&](const uint32_t (&y)[12], int n, int on, uint64_t p16, uint64_t p8) {
      if (n == 0) st128<0>(p16, on, y[0], y[1], y[2], y[3]);
      if (n == 1) st128<192>(p16, on, y[6], y[7], y[8], y[9]);
      if (n == 2) st64<0>(p8, on, y[4], y[5]);
      if (n == 3) st64<192>(p8, on, y[10], y[11]);
    };
    auto load = [&](int cg) { ldsm4(A[cg % NAB], la[cg] + soff); ldsm4(B[cg % NAB], la[cg] + soff + ROW_PITCH); };
    uint32_t clk = 0;
    auto prep = [&](int r) {
#pragma unroll
      for (int i = 0; i < 4; ++i) {
        const int src = ((r - 1) & ~1) + (i >> 1), k = 1 + (i & 1);
        if (r < 12) S[r % 3][i] = hadd2(A[r % NAB][i], B[r % NAB][i]);
        if (r > 0) MP[r % 3][i] = copy32((r & 1) ? A[src % NAB][k] : S[src % 3][k], zero2);
        if (r < 12) D[r % 3][i] = hsub2(A[r % NAB][i], B[r % NAB][i]);
        if (r > 0) {
          const uint32_t v = (r & 1) ? B[src % NAB][k] : D[src % 3][k];
          if (i == 3 && r >= 2) asm volatile("lop3.b32 %0, %1, %2, %3, 0xF8;" : "=r"(MQ[r % 3][i]) : "r"(v), "r"(clk), "r"(zero2));
          else MQ[r % 3][i] = copy32(v, zero2);
        }
      }
    };

#pragma unroll
    for (int i = 0; i < 4; ++i) { A[11 % NAB][i] = 0; B[11 % NAB][i] = 0; S[11 % 3][i] = 0; D[11 % 3][i] = 0; MP[12 % 3][i] = 0; MQ[12 % 3][i] = 0; }

    for (int t = 0; t < NB; ++t) {
      uint32_t yo[12], ye[12];
#pragma unroll
      for (int i = 0; i < 4; ++i) {
        yo[i] = A[11 % NAB][i]; yo[6 + i] = B[11 % NAB][i]; ye[i] = S[11 % 3][i]; ye[6 + i] = D[11 % 3][i];
        yo[4 + (i & 1) + 6 * (i >> 1)] = MP[12 % 3][i]; ye[4 + (i & 1) + 6 * (i >> 1)] = MQ[12 % 3][i];
      }
      auto block = [&](int k) {
        const uint32_t z = (k & 1) ? zero : zero2;
        if (k >= 10 ? t > (int)z : z == 0) {
          float ev[2];
#pragma unroll
          for (int u = 0; u < 2; ++u) {
            const int e = k / 6, j = k % 6, i = 4 * j + 2 * e + u;
            if (u == 0) yo[k] = pack_bf16(Z0[i], Z0[i + 1]);
            const float sm = Z1[i] + Z2[i], df = Z1[i] - Z2[i];
            const float p = fmaf(0.5f, sm, -Z0[i]);
            ev[u] = fmaf(0.5f, df, -Z3[i]);
            Z0[i] = p;
            Z1[i] = (p + b2[2 * j + u]) + Z3[i];
            Z2[i] = p - Z3[i];
            if (u == 1) ye[k] = pack_bf16(ev[0], ev[1]);
            if (j == 3 && u == 0) store(yo, e, t - 1, op16, op8);
            if (j == 4 && u == 0) store(ye, e, t - 1, oq16, oq8);
            if (j == 5 && u == 0) store(yo, 2 + e, t - 1, op16, op8);
            if (j == 5 && u == 1) store(ye, 2 + e, t - 1, oq16, oq8);
            if (k == 0 && u == 0) { advance(op16); advance(op8); }
            if (k == 1 && u == 0) { advance(oq16); advance(oq8); }
          }
        }
      };
      if (t > 0) {
#pragma unroll
        for (int k = 0; k < 10; ++k) block(k);
      }
      soff = wg * RING_BYTES + (t & 1) * STAGE_BYTES;
      if (wg) asm volatile("bar.sync 1, 288;" ::: "memory"); else asm volatile("bar.sync 2, 288;" ::: "memory");
      static_assert(LDA == 3, "three channel groups are loaded ahead of the main loop");
      load(0);
      block(10);
      load(1);
      block(11);
      if (t == 1) {
        const uint32_t xch = sbase + XCH_OFF + (tid & 127) * 16;
        auto put = [&](int n, uint32_t a, uint32_t b, uint32_t c, uint32_t d) {
          asm volatile("st.shared.v4.b32 [%0], {%1,%2,%3,%4};" ::"r"(xch + n * 2048), "r"(a), "r"(b), "r"(c), "r"(d) : "memory");
        };
        put(0, ye[0], ye[1], ye[2], ye[3]); put(1, ye[6], ye[7], ye[8], ye[9]);
        put(3, yo[0], yo[1], yo[2], yo[3]); put(4, yo[6], yo[7], yo[8], yo[9]);
        const uint32_t x2 = wg ? sbase + ROW_TX + w * ROW_PITCH + lane * 16 : xch + 2 * 2048, x5 = x2 + (wg ? 4 * ROW_PITCH : 3 * 2048);
        asm volatile("st.shared.v4.b32 [%0], {%1,%2,%3,%4};" ::"r"(x2), "r"(ye[4]), "r"(ye[5]), "r"(ye[10]), "r"(ye[11]) : "memory");
        asm volatile("st.shared.v4.b32 [%0], {%1,%2,%3,%4};" ::"r"(x5), "r"(yo[4]), "r"(yo[5]), "r"(yo[10]), "r"(yo[11]) : "memory");
        asm volatile("bar.arrive 3, 192;" ::: "memory");
      }
      load(2);
      prep(0);
      const uint64_t dbase = WDESC + (uint64_t)(t & zero), db0 = dbase - dswap, db3 = dbase + dswap;
      wg_fence();
#pragma unroll
      for (int r = 0; r < 13; ++r) {
        if (r < 12) {
          mma48<1>(Z0, A[r % NAB], db0, d_outer(r, 0));
          mma48<1>(Z1, S[r % 3], dbase, d_outer(r, 1));
          mma48<1>(Z2, D[r % 3], dbase, d_outer(r, 2));
          if (r == 0) mma48<0>(Z3, B[r % NAB], db3, d_outer(r, 3));
          else mma48<1>(Z3, B[r % NAB], db3, d_outer(r, 3));
        }
        if (r > 0) {
          const int c = (r - 1) >> 1;
          if (r & 1) { mma48<1>(Z0, MP[r % 3], db0, d_mid(c, 0)); mma48<1>(Z3, MQ[r % 3], db3, d_mid(c, 3)); }
          else       { mma48<1>(Z1, MP[r % 3], dbase, d_mid(c, 1)); mma48<1>(Z2, MQ[r % 3], dbase, d_mid(c, 2)); }
        }
        wg_commit();
        if (r + LDA < 12) load(r + LDA);
        if (r == GATE_R) { if (wg) asm volatile("bar.arrive 2, 288;" ::: "memory"); else asm volatile("bar.arrive 1, 288;" ::: "memory"); }
        if (r == 11) { if (wg) asm volatile("bar.arrive 7, 160;" ::: "memory"); else asm volatile("bar.arrive 6, 160;" ::: "memory"); }
        if (r < 12) {
          prep(r + 1);
          if (r == 7 && t + wg == 0) asm volatile("bar.sync 5, 256;" ::: "memory");
          wg_fence();
          wg_wait<1>();
          if (r < 11) asm volatile("mov.u32 %0, %clock;" : "=r"(clk) :: "memory");
        } else {
          wg_wait<0>();
        }
      }
      pin(Z0); pin(Z1); pin(Z2); pin(Z3);
    }
    advance(op16); advance(op8);

    {
      uint32_t yo[12], ye[12], F[12][4], M[6][4];
      float T[24];
      auto rows = [&]() {
#pragma unroll
        for (int k = 0; k < 12; ++k) yo[k] = pack_bf16(Z0[4 * (k % 6) + 2 * (k / 6)], Z0[4 * (k % 6) + 2 * (k / 6) + 1]);
#pragma unroll
        for (int n = 0; n < 4; ++n) store(yo, n, 1, op16, op8);
#pragma unroll
        for (int j = 0; j < 6; ++j) {
          sched_fence();
          float ev[4];
#pragma unroll
          for (int u = 0; u < 4; ++u) {
            const int i = 4 * j + u;
            ev[u] = fmah(fsub(Z1[i], Z2[i]), Z3[i]);
            Z0[i] = fmah(fadd(Z1[i], Z2[i]), Z0[i]);
          }
          ye[j] = pack_bf16(ev[0], ev[1]); ye[6 + j] = pack_bf16(ev[2], ev[3]);
          if (j == 3) { store(ye, 0, 1, op16 + orow, op8 + orow); store(ye, 1, 1, op16 + orow, op8 + orow); }
          if (j == 5) { store(ye, 2, 1, op16 + orow, op8 + orow); store(ye, 3, 1, op16 + orow, op8 + orow); }
        }
        sched_fence();
      };
      if (wg == 0) {
        rows();
        asm volatile("bar.sync 2, 288;" ::: "memory");
        asm volatile("bar.arrive 1, 288;" ::: "memory");
      } else {
        asm volatile("bar.sync 1, 288;" ::: "memory");
      }
#pragma unroll
      for (int cg = 0; cg < 12; ++cg) ldsm4(F[cg], la[cg] + wg * RING_BYTES + (NB & 1) * STAGE_BYTES);
      const uint64_t d0 = WDESC - dswap + zero2;
#pragma unroll
      for (int c = 0; c < 6; ++c) {
        M[c][0] = copy32(F[2 * c][1], zero2); M[c][1] = copy32(F[2 * c][2], zero2);
        M[c][2] = copy32(F[2 * c + 1][1], zero2); M[c][3] = copy32(F[2 * c + 1][2], zero2);
      }
      wg_fence();
#pragma unroll
      for (int c = 0; c < 6; ++c) {
        if (c == 0) mma48<0>(T, F[0], d0, d_outer(0, 0));
        else mma48<1>(T, F[2 * c], d0, d_outer(2 * c, 0));
        mma48<1>(T, F[2 * c + 1], d0, d_outer(2 * c + 1, 0));
        mma48<1>(T, M[c], d0, d_mid(c, 0));
      }
      wg_commit();
      if (wg == 1) rows();
      wg_wait<0>();
      pin(T);
#pragma unroll
      for (int k = 0; k < 12; ++k) {
        const int i = 4 * (k % 6) + 2 * (k / 6);
        yo[k] = pack_bf16(Z0[i] + T[i], Z0[i + 1] + T[i + 1]);
      }
#pragma unroll
      for (int n = 0; n < 4; ++n) store(yo, n, 1, op16 + 2 * orow, op8 + 2 * orow);
    }
  }
}

typedef CUresult (*EncodeTiledFn)(CUtensorMap*, CUtensorMapDataType, cuuint32_t, void*, const cuuint64_t*,
                                  const cuuint64_t*, const cuuint32_t*, const cuuint32_t*, CUtensorMapInterleave,
                                  CUtensorMapSwizzle, CUtensorMapL2promotion, CUtensorMapFloatOOBfill);

}

extern "C" void kernel_launch(void* const* d_in, const int* in_sizes, int n_in, void* d_out, int out_size) {
  (void)in_sizes; (void)n_in; (void)out_size;
  static EncodeTiledFn encode = nullptr;
  if (!encode) {
    void* fn = nullptr;
    cudaDriverEntryPointQueryResult qr;
    cudaGetDriverEntryPoint("cuTensorMapEncodeTiled", &fn, cudaEnableDefault, &qr);
    encode = (EncodeTiledFn)fn;
    cudaFuncSetAttribute(conv3x3_kernel, cudaFuncAttributeMaxDynamicSharedMemorySize, SMEM_BYTES);
  }
  CUtensorMap xmap;
  const cuuint64_t dims[3] = {64, (cuuint64_t)(OROW / 128), (cuuint64_t)IMG_H};
  const cuuint64_t strides[2] = {128, (cuuint64_t)OROW};
  const cuuint32_t box[3] = {64, ROW_LINES, 1};
  const cuuint32_t estr[3] = {1, 1, 1};
  encode(&xmap, CU_TENSOR_MAP_DATA_TYPE_BFLOAT16, 3, d_in[0], dims, strides, box, estr, CU_TENSOR_MAP_INTERLEAVE_NONE,
         CU_TENSOR_MAP_SWIZZLE_128B, CU_TENSOR_MAP_L2_PROMOTION_L2_256B, CU_TENSOR_MAP_FLOAT_OOB_FILL_NONE);
  CUtensorMap wmap;
  const cuuint64_t wdims[3] = {64, CH * CH * 2 / 128, 9};
  const cuuint64_t wstrides[2] = {128, CH * CH * 2};
  const cuuint32_t wbox[3] = {64, W_TAP / 128, 9};
  encode(&wmap, CU_TENSOR_MAP_DATA_TYPE_BFLOAT16, 3, d_in[1], wdims, wstrides, wbox, estr, CU_TENSOR_MAP_INTERLEAVE_NONE,
         CU_TENSOR_MAP_SWIZZLE_NONE, CU_TENSOR_MAP_L2_PROMOTION_L2_256B, CU_TENSOR_MAP_FLOAT_OOB_FILL_NONE);
  conv3x3_kernel<<<128, NUM_THREADS, SMEM_BYTES, cudaStreamPerThread>>>(
      xmap, wmap, (const uint8_t*)d_in[0], (const uint8_t*)d_in[1], (const __nv_bfloat16*)d_in[2], (__nv_bfloat16*)d_out, 0u, 0u);
}
```
